```python
import torch

def _softmax(x, axis=-1):
    return torch.softmax(x, dim=axis)
def _gelu(x):
    return torch.nn.functional.gelu(x, approximate="tanh")
def _silu(x):
    return torch.nn.functional.silu(x)
def _sigmoid(x):
    return torch.sigmoid(x)
def _layernorm(x, axis=-1, eps=1e-5):
    m = x.mean(dim=axis, keepdim=True)
    v = x.var(dim=axis, keepdim=True, unbiased=False)
    return (x - m) / torch.sqrt(v + eps)
def _scatter_add(tgt, idx, src, axis=0):
    return tgt.clone().index_add_(axis, idx, src)
def _segment_sum(src, seg, n):
    out = torch.zeros((n,) + src.shape[1:], dtype=src.dtype)
    return out.index_add_(0, seg, src)
def _pad(x, pw):
    flat = tuple(v for pair in reversed(pw) for v in pair)
    return torch.nn.functional.pad(x, flat)

kernel_name = 'sequential_preLN__gqa_block_cached__mixer_token_mlp__decode'

def setup_inputs():

    _w = (lambda a: (lambda t: t.to(torch.bfloat16) if t.is_floating_point() else t)(torch.as_tensor(a)))
    def _A_setup():
        B, Sq, D = 8, 1, 448
        Hq, Hkv, Sk, Dh = 16, 8, 8192, 256
        assert Hq % Hkv == 0, (Hq, Hkv)
        return {
            "x": _w((lambda *s: torch.randn(*s, dtype=torch.bfloat16) * 0.05)(B, Sq, D)),
            "k_cache": _w((lambda *s: torch.randn(*s, dtype=torch.bfloat16) * 1.6)(B, Hkv, Sk, Dh)),
            "v_cache": _w((lambda *s: torch.randn(*s, dtype=torch.bfloat16) * 0.8)(B, Hkv, Sk, Dh)),
            "wq": _w((lambda *s: torch.randn(*s, dtype=torch.bfloat16) * 1.6)(D, Hq * Dh) * (D ** -0.5)),
            "wo": _w((lambda *s: torch.randn(*s, dtype=torch.bfloat16) * 0.8)(Hq * Dh, D) * ((Hq * Dh) ** -0.5)),
        }
    _A_in = _A_setup()

    def _B_setup():
        B, S, D, F = 8, 1, 448, 1792
        return {
            "x": _w((lambda *s: torch.randn(*s, dtype=torch.bfloat16) * 0.05)(B, S, D)),
            "w1": _w((lambda *s: torch.randn(*s, dtype=torch.bfloat16) * 0.4)(S, F) * (S ** -0.5)),
            "b1": _w((lambda *s: torch.randn(*s, dtype=torch.bfloat16) * 0.4)(F) * 0.02),
            "w2": _w((lambda *s: torch.randn(*s, dtype=torch.bfloat16) * 0.4)(F, S) * (F ** -0.5)),
            "b2": _w((lambda *s: torch.randn(*s, dtype=torch.bfloat16) * 0.4)(S) * 0.02),
        }
    _B_in = _B_setup()

    return {
        "A_x": _A_in["x"],
        "A_k_cache": _A_in["k_cache"],
        "A_v_cache": _A_in["v_cache"],
        "A_wq": _A_in["wq"],
        "A_wo": _A_in["wo"],
        "B_x": _B_in["x"],
        "B_w1": _B_in["w1"],
        "B_b1": _B_in["b1"],
        "B_w2": _B_in["w2"],
        "B_b2": _B_in["b2"],
    }

def reference(A_x, A_k_cache, A_v_cache, A_wq, A_wo, B_x, B_w1, B_b1, B_w2, B_b2):
    def _A_ref(x, k_cache, v_cache, wq, wo):
        B, Sq, D = x.shape
        Hq, Dh = 16, 256
        Hkv = k_cache.shape[1]
        rep = Hq // Hkv
        q = (lambda x, *d: x.permute(*d))((x @ wq).reshape(B, Sq, Hq, Dh), 0, 2, 1, 3)
        k = (lambda x, n, axis: torch.repeat_interleave(x, n, dim=axis))(k_cache, rep, axis=1)
        v = (lambda x, n, axis: torch.repeat_interleave(x, n, dim=axis))(v_cache, rep, axis=1)
        scores = torch.einsum("bhqd,bhkd->bhqk", q, k) * (Dh ** -0.5)
        p = _softmax(scores, axis=-1)
        o = torch.einsum("bhqk,bhkd->bhqd", p, v)
        return (lambda x, *d: x.permute(*d))(o, 0, 2, 1, 3).reshape(B, Sq, Hq * Dh) @ wo

    def _B_ref(x, w1, b1, w2, b2):
        B, S, D = x.shape
        h = _layernorm(x, axis=-1)
        u = torch.einsum("bsd,sf->bdf", h, w1) + b1
        u = _gelu(u)
        y = torch.einsum("bdf,fs->bds", u, w2) + b2
        return (lambda x, *d: x.permute(*d))(y, 0, 2, 1)

    x = A_x
    h = x + _A_ref(_layernorm(x, axis=-1), A_k_cache, A_v_cache, A_wq, A_wo)
    h2 = h + _B_ref(_layernorm(h, axis=-1), B_w1, B_b1, B_w2, B_b2)
    return h2
```

```cpp
#include <cuda_runtime.h>
#include <cuda_bf16.h>
#include <stdint.h>

namespace {

constexpr int NB = 8, DM = 448, SK = 8192, DH = 256, FF = 1792;
constexpr int NPAIR = 64;
constexpr int UNIT_KEYS = 64;
constexpr int UPP = SK / UNIT_KEYS;
constexpr int NHALF = NPAIR * UPP;
constexpr int NUNITS = 2 * NHALF;
constexpr int TILE_BYTES = UNIT_KEYS * DH * 2;
constexpr int AUX_BYTES = 1024;
constexpr int RING = 5;
constexpr int DEPTH = 2;
constexpr int NREP = 2;
constexpr int WO_BYTES = 32 * DM * 2;
constexpr int MLPW_BYTES = FF * 2;
constexpr int SMEM_BYTES = RING * (TILE_BYTES + AUX_BYTES) + WO_BYTES + 3 * MLPW_BYTES;
constexpr int NTHREADS = 320;
constexpr int FIFO_N = 32;
constexpr int CPAD = 32;
constexpr int EMPTY = -2, SENTINEL = -1;

__device__ __align__(1024) __nv_bfloat16 g_q[NB * 4096];
__device__ __align__(1024) uint4 g_S[NPAIR * 2048];
__device__ __align__(1024) float g_O[NREP * NPAIR * 512];
__device__ __align__(1024) float g_h[NB * DM];
__device__ __align__(1024) unsigned g_cnt[(64 * 3 + 8 + 1) * CPAD];
__device__ __align__(128) unsigned g_work[CPAD];
__device__ __align__(128) unsigned g_qready[CPAD];
__device__ __align__(128) unsigned g_exit[CPAD];

__device__ __forceinline__ unsigned* cntK(int p) { return g_cnt + (p)*CPAD; }
__device__ __forceinline__ unsigned* flagP(int p) { return g_cnt + (64 + p) * CPAD; }
__device__ __forceinline__ unsigned* cntV(int p) { return g_cnt + (128 + p) * CPAD; }
__device__ __forceinline__ unsigned* cntH(int b) { return g_cnt + (192 + b) * CPAD; }
__device__ __forceinline__ unsigned* cntL() { return g_cnt + (200) * CPAD; }

__device__ __forceinline__ uint32_t smem_u32(const void* p) { return (uint32_t)__cvta_generic_to_shared(p); }
__device__ __forceinline__ void mbar_init(uint32_t bar, uint32_t cnt) {
    asm volatile("mbarrier.init.shared::cta.b64 [%0], %1;" ::"r"(bar), "r"(cnt) : "memory");
}
__device__ __forceinline__ void mbar_expect_tx(uint32_t bar, uint32_t bytes) {
    asm volatile("mbarrier.arrive.expect_tx.shared::cta.b64 _, [%0], %1;" ::"r"(bar), "r"(bytes) : "memory");
}
__device__ __forceinline__ void mbar_arrive(uint32_t bar) {
    asm volatile("mbarrier.arrive.shared::cta.b64 _, [%0];" ::"r"(bar) : "memory");
}
__device__ __forceinline__ bool mbar_try(uint32_t bar, uint32_t parity) {
    uint32_t done;
    asm volatile(
        "{\n.reg .pred p;\nmbarrier.try_wait.parity.shared::cta.b64 p, [%1], %2;\nselp.u32 %0, 1, 0, p;\n}"
        : "=r"(done)
        : "r"(bar), "r"(parity)
        : "memory");
    return done != 0;
}
constexpr long long SPIN_LIMIT = 4000000000LL;
__device__ __forceinline__ void mbar_wait(uint32_t bar, uint32_t parity) {
    if (mbar_try(bar, parity)) return;
    long long t0 = clock64();
    while (!mbar_try(bar, parity)) {
        if (clock64() - t0 > SPIN_LIMIT) __trap();
    }
}
__device__ __forceinline__ void bulk_load(uint32_t dst, const void* src, uint32_t bytes, uint32_t bar, uint64_t pol) {
    asm volatile(
        "cp.async.bulk.shared::cluster.global.mbarrier::complete_tx::bytes.L2::cache_hint [%0], [%1], %2, [%3], %4;" ::"r"(dst),
        "l"(src), "r"(bytes), "r"(bar), "l"(pol)
        : "memory");
}
__device__ __forceinline__ void bulk_load_nohint(uint32_t dst, const void* src, uint32_t bytes, uint32_t bar) {
    asm volatile("cp.async.bulk.shared::cluster.global.mbarrier::complete_tx::bytes [%0], [%1], %2, [%3];" ::"r"(dst),
                 "l"(src), "r"(bytes), "r"(bar)
                 : "memory");
}
__device__ __forceinline__ void cp_async16(uint32_t dst, const void* src) {
    asm volatile("cp.async.cg.shared.global [%0], [%1], 16;" ::"r"(dst), "l"(src) : "memory");
}
__device__ __forceinline__ void cp_async_arrive_noinc(uint32_t bar) {
    asm volatile("cp.async.mbarrier.arrive.noinc.shared::cta.b64 [%0];" ::"r"(bar) : "memory");
}
__device__ __forceinline__ unsigned ld_acquire_gpu(const unsigned* p) {
    unsigned v;
    asm volatile("ld.acquire.gpu.global.u32 %0, [%1];" : "=r"(v) : "l"(p) : "memory");
    return v;
}
__device__ __forceinline__ void red_add_gpu(unsigned* p, unsigned v) {
    asm volatile("red.relaxed.gpu.global.add.u32 [%0], %1;" ::"l"(p), "r"(v) : "memory");
}
__device__ __forceinline__ unsigned atom_add_acqrel_gpu(unsigned* p, unsigned v) {
    unsigned o;
    asm volatile("atom.acq_rel.gpu.global.add.u32 %0, [%1], %2;" : "=r"(o) : "l"(p), "r"(v) : "memory");
    return o;
}
__device__ __forceinline__ void red_add_v4(float* p, float a, float b, float c, float d) {
    asm volatile("red.relaxed.gpu.global.add.v4.f32 [%0], {%1,%2,%3,%4};" ::"l"(p), "f"(a), "f"(b), "f"(c), "f"(d) : "memory");
}
__device__ __forceinline__ int ld_acquire_cta_s(uint32_t a) {
    int v;
    asm volatile("ld.acquire.cta.shared::cta.s32 %0, [%1];" : "=r"(v) : "r"(a) : "memory");
    return v;
}
__device__ __forceinline__ void st_release_cta_s(uint32_t a, int v) {
    asm volatile("st.release.cta.shared::cta.s32 [%0], %1;" ::"r"(a), "r"(v) : "memory");
}
__device__ __forceinline__ int atom_add_acqrel_cta_s(uint32_t a, int v) {
    int o;
    asm volatile("atom.acq_rel.cta.shared::cta.add.s32 %0, [%1], %2;" : "=r"(o) : "r"(a), "r"(v) : "memory");
    return o;
}
__device__ __forceinline__ void bar_sync(int id, int n) { asm volatile("bar.sync %0, %1;" ::"r"(id), "r"(n) : "memory"); }
__device__ __forceinline__ void ldsm4(uint32_t (&r)[4], uint32_t addr) {
    asm volatile("ldmatrix.sync.aligned.m8n8.x4.shared.b16 {%0,%1,%2,%3}, [%4];"
                 : "=r"(r[0]), "=r"(r[1]), "=r"(r[2]), "=r"(r[3])
                 : "r"(addr)
                 : "memory");
}
__device__ __forceinline__ void ldsm4t(uint32_t (&r)[4], uint32_t addr) {
    asm volatile("ldmatrix.sync.aligned.m8n8.x4.trans.shared.b16 {%0,%1,%2,%3}, [%4];"
                 : "=r"(r[0]), "=r"(r[1]), "=r"(r[2]), "=r"(r[3])
                 : "r"(addr)
                 : "memory");
}
__device__ __forceinline__ void mma16816(float (&c)[4], const uint32_t (&a)[4], uint32_t b0, uint32_t b1) {
    asm volatile(
        "mma.sync.aligned.m16n8k16.row.col.f32.bf16.bf16.f32 {%0,%1,%2,%3}, {%4,%5,%6,%7}, {%8,%9}, {%0,%1,%2,%3};"
        : "+f"(c[0]), "+f"(c[1]), "+f"(c[2]), "+f"(c[3])
        : "r"(a[0]), "r"(a[1]), "r"(a[2]), "r"(a[3]), "r"(b0), "r"(b1));
}
__device__ __forceinline__ float bf16r(float x) { return __bfloat162float(__float2bfloat16_rn(x)); }
__device__ __forceinline__ float bf_lo(uint32_t w) { return __uint_as_float(w << 16); }
__device__ __forceinline__ float bf_hi(uint32_t w) { return __uint_as_float(w & 0xffff0000u); }
__device__ __forceinline__ uint32_t pack_bf16(float lo, float hi) {
    uint32_t r;
    asm("cvt.rn.bf16x2.f32 %0, %1, %2;" : "=r"(r) : "f"(hi), "f"(lo));
    return r;
}
__device__ __forceinline__ float ex2f(float x) {
    float y;
    asm("ex2.approx.ftz.f32 %0, %1;" : "=f"(y) : "f"(x));
    return y;
}
__device__ __forceinline__ float tanh_fast(float x) {
    float y;
    asm("tanh.approx.f32 %0, %1;" : "=f"(y) : "f"(x));
    return y;
}
__device__ __forceinline__ uint32_t hmax2_bf16(uint32_t a, uint32_t b) {
    uint32_t r;
    asm("max.bf16x2 %0, %1, %2;" : "=r"(r) : "r"(a), "r"(b));
    return r;
}
__device__ __forceinline__ uint32_t hmul2_bf16(uint32_t a, uint32_t b) {
    uint32_t r;
    asm("mul.rn.bf16x2 %0, %1, %2;" : "=r"(r) : "r"(a), "r"(b));
    return r;
}
__device__ __forceinline__ uint32_t hadd2_bf16(uint32_t a, uint32_t b) {
    uint32_t r;
    asm("add.rn.bf16x2 %0, %1, %2;" : "=r"(r) : "r"(a), "r"(b));
    return r;
}
__device__ __forceinline__ float warp_sum(float v) {
#pragma unroll
    for (int o = 16; o > 0; o >>= 1) v += __shfl_xor_sync(0xffffffffu, v, o);
    return v;
}

__device__ __forceinline__ void ln_stats(const float (&v)[14], float shift, float& m, float& den) {
    float s1 = 0.f, s2 = 0.f;
#pragma unroll
    for (int i = 0; i < 14; i++) {
        float d = v[i] - shift;
        s1 += d;
        s2 = fmaf(d, d, s2);
    }
#pragma unroll
    for (int o = 16; o > 0; o >>= 1) {
        s1 += __shfl_xor_sync(0xffffffffu, s1, o);
        s2 += __shfl_xor_sync(0xffffffffu, s2, o);
    }
    const float inv = 1.0f / (float)DM;
    float md = s1 * inv;
    float var = fmaxf(s2 * inv - md * md, 0.f);
    m = bf16r(shift + md);
    den = bf16r(sqrtf(bf16r(bf16r(var) + 1e-5f)));
}
__device__ __forceinline__ float ln_apply(float x, float m, float den) { return bf16r(__fdiv_rn(bf16r(x - m), den)); }

struct Params {
    const __nv_bfloat16* x;
    const char* K;
    const char* V;
    const __nv_bfloat16* wq;
    const __nv_bfloat16* wo;
    const __nv_bfloat16* w1;
    const __nv_bfloat16* b1;
    const __nv_bfloat16* w2;
    const __nv_bfloat16* b2;
    __nv_bfloat16* out;
};

__global__ void __launch_bounds__(NTHREADS, 1) fused_decode_kernel(const Params prm) {
    extern __shared__ __align__(1024) unsigned char smem[];
    __shared__ __align__(8) uint64_t s_fullT[RING], s_fullA[RING], s_empty[RING], s_wobar;
    __shared__ int s_unit[RING], s_cnt[RING];
    __shared__ int s_fifo[FIFO_N], s_fifo_head;
    __shared__ int s_lj[64], s_sigdone, s_phase2;
    __shared__ int s_job[2];
    __shared__ float s_o[32];
    __shared__ uint32_t s_redu[8];
    __shared__ float s_redf[8];

    const int tid = threadIdx.x, warp = tid >> 5, lane = tid & 31;
    const int cta = blockIdx.x, G = gridDim.x;
    const uint32_t sm_tiles = smem_u32(smem);
    const uint32_t sm_aux = sm_tiles + RING * TILE_BYTES;
    unsigned char* wo_s = smem + RING * (TILE_BYTES + AUX_BYTES);

    if (warp == 8) {
        uint64_t pol = 0;
        int u_cur = cta, u_next = 0;
        if (lane == 0) {
            for (int s = 0; s < RING; s++) {
                mbar_init(smem_u32(&s_fullT[s]), 1);
                mbar_init(smem_u32(&s_fullA[s]), 32);
                mbar_init(smem_u32(&s_empty[s]), 4);
                s_cnt[s] = 0;
            }
            mbar_init(smem_u32(&s_wobar), 1);
            asm volatile("fence.mbarrier_init.release.cluster;" ::: "memory");
            asm volatile("fence.proxy.async.shared::cta;" ::: "memory");
            asm volatile("createpolicy.fractional.L2::evict_first.b64 %0, 1.0;" : "=l"(pol));
#pragma unroll
            for (int k = 0; k < DEPTH; k++) {
                s_unit[k] = cta + k * G;
                mbar_expect_tx(smem_u32(&s_fullT[k]), TILE_BYTES);
                bulk_load(sm_tiles + k * TILE_BYTES, prm.K + (size_t)(cta + k * G) * TILE_BYTES, TILE_BYTES, smem_u32(&s_fullT[k]), pol);
            }
            u_cur = (int)atomicAdd(g_work, 1u) + DEPTH * G;
            u_next = (int)atomicAdd(g_work, 1u) + DEPTH * G;
        }
        s_fifo[lane] = EMPTY;
        s_lj[lane] = EMPTY;
        s_lj[lane + 32] = EMPTY;
        if (lane == 0) { s_fifo_head = 0; s_sigdone = 0; s_phase2 = 0; }
        __syncthreads();

        int i = DEPTH;
        if (lane == 0) {
            while (i < RING) {
                if (ld_acquire_gpu(g_qready) >= (unsigned)G) break;
                mbar_wait(smem_u32(&s_fullT[i - DEPTH]), 0);
                s_unit[i] = u_cur;
                mbar_expect_tx(smem_u32(&s_fullT[i]), TILE_BYTES);
                bulk_load(sm_tiles + i * TILE_BYTES, prm.K + (size_t)u_cur * TILE_BYTES, TILE_BYTES, smem_u32(&s_fullT[i]), pol);
                u_cur = u_next;
                u_next = (int)atomicAdd(g_work, 1u) + DEPTH * G;
                i++;
            }
            long long t0 = clock64();
            while (ld_acquire_gpu(g_qready) < (unsigned)G) {
                if (clock64() - t0 > SPIN_LIMIT) __trap();
            }
        }
        __syncwarp();
        i = __shfl_sync(0xffffffffu, i, 0);
        for (int s = 0; s < i; s++) {
            int pair = s_unit[s] / UPP;
            const char* src = (const char*)g_q + (size_t)pair * 1024;
            cp_async16(sm_aux + s * AUX_BYTES + lane * 16, src + lane * 16);
            cp_async16(sm_aux + s * AUX_BYTES + 512 + lane * 16, src + 512 + lane * 16);
            cp_async_arrive_noinc(smem_u32(&s_fullA[s]));
        }
        bool allL = false;
        int s = i % RING, n = i / RING;
        int ls = (i - DEPTH) % RING, ln = (i - DEPTH) / RING;
        while (true) {
            int u = __shfl_sync(0xffffffffu, u_cur, 0);
            if (u >= NUNITS) break;
            if (lane == 0) {
                mbar_wait(smem_u32(&s_empty[s]), (n & 1) ^ 1);
                mbar_wait(smem_u32(&s_fullT[ls]), ln & 1);
                s_unit[s] = u;
                mbar_expect_tx(smem_u32(&s_fullT[s]), TILE_BYTES);
                const char* src = (u < NHALF) ? prm.K + (size_t)u * TILE_BYTES : prm.V + (size_t)(u - NHALF) * TILE_BYTES;
                bulk_load(sm_tiles + s * TILE_BYTES, src, TILE_BYTES, smem_u32(&s_fullT[s]), pol);
                u_cur = u_next;
                u_next = (int)atomicAdd(g_work, 1u) + DEPTH * G;
                if (u >= NHALF && !allL) {
                    s_phase2 = 1;
                    if (ld_acquire_gpu(cntL()) >= (unsigned)NPAIR) {
                        allL = true;
                    } else {
                        long long t0 = clock64();
                        const unsigned* f = flagP((u - NHALF) / UPP);
                        while (ld_acquire_gpu(f) == 0u) {
                            if (clock64() - t0 > SPIN_LIMIT) __trap();
                        }
                    }
                }
            }
            __syncwarp();
            if (u < NHALF) {
                const char* src = (const char*)g_q + (size_t)(u / UPP) * 1024;
                cp_async16(sm_aux + s * AUX_BYTES + lane * 16, src + lane * 16);
                cp_async16(sm_aux + s * AUX_BYTES + 512 + lane * 16, src + 512 + lane * 16);
            } else if (lane < 16) {
                const char* src = (const char*)g_S + (size_t)(u - NHALF) * 256;
                cp_async16(sm_aux + s * AUX_BYTES + lane * 16, src + lane * 16);
            }
            cp_async_arrive_noinc(smem_u32(&s_fullA[s]));
            if (++ls == RING) { ls = 0; ln++; }
            if (++s == RING) { s = 0; n++; }
        }
        if (lane == 0) {
            s_phase2 = 1;
            mbar_wait(smem_u32(&s_empty[s]), (n & 1) ^ 1);
            s_unit[s] = SENTINEL;
            mbar_arrive(smem_u32(&s_fullT[s]));
        }
    } else if (warp == 9) {
        __syncthreads();
        if (lane == 0) {
            int tail = 0, ljn = 0;
            bool done = false;
            while (!done) {
                int e;
                long long t0 = clock64();
                while ((e = ld_acquire_cta_s(smem_u32(&s_fifo[tail % FIFO_N]))) == EMPTY) {
                    __nanosleep(32);
                    if (clock64() - t0 > SPIN_LIMIT) __trap();
                }
                int ent[4];
                int cnt = 0;
                ent[0] = e; ent[1] = EMPTY; ent[2] = EMPTY; ent[3] = EMPTY;
                cnt = 1;
#pragma unroll
                for (int k = 1; k < 4; k++) {
                    if (cnt == k) {
                        int e2 = ld_acquire_cta_s(smem_u32(&s_fifo[(tail + k) % FIFO_N]));
                        if (e2 != EMPTY) { ent[k] = e2; cnt = k + 1; }
                    }
                }
                __threadfence();
                unsigned old[4];
#pragma unroll
                for (int k = 0; k < 4; k++) {
                    old[k] = 0;
                    if (k < cnt && ent[k] >= 0) {
                        if (ent[k] < NHALF) old[k] = atomicAdd(cntK(ent[k] / UPP), 1u);
                        else red_add_gpu(cntV((ent[k] - NHALF) / UPP), 1u);
                    }
                }
#pragma unroll
                for (int k = 0; k < 4; k++) {
                    if (k < cnt) {
                        if (ent[k] == SENTINEL) done = true;
                        else if (ent[k] < NHALF && old[k] == (unsigned)(UPP - 1)) {
                            __threadfence();
                            st_release_cta_s(smem_u32(&s_lj[ljn]), ent[k] / UPP);
                            ljn++;
                        }
                        st_release_cta_s(smem_u32(&s_fifo[(tail + k) % FIFO_N]), EMPTY);
                    }
                }
                tail += cnt;
            }
            st_release_cta_s(smem_u32(&s_sigdone), 1);
        }
    } else {
        {
            float* s_xn = (float*)wo_s;
            float* s_red = (float*)(wo_s + 14336);
            uint4 wv[7];
            const int c = tid & 3, r0 = tid >> 2;
            if (cta < 128) {
#pragma unroll
                for (int i = 0; i < 7; i++) {
                    const uint4* p = (const uint4*)(prm.wq + (size_t)(r0 + 64 * i) * 4096 + cta * 32 + c * 8);
                    asm volatile("ld.global.nc.L1::no_allocate.v4.u32 {%0,%1,%2,%3}, [%4];"
                                 : "=r"(wv[i].x), "=r"(wv[i].y), "=r"(wv[i].z), "=r"(wv[i].w)
                                 : "l"(p));
                }
            }
            uint32_t xw[7];
            {
                const uint32_t* xr = (const uint32_t*)(prm.x + warp * DM);
#pragma unroll
                for (int i = 0; i < 7; i++)
                    asm volatile("ld.global.nc.u32 %0, [%1];" : "=r"(xw[i]) : "l"(xr + lane + 32 * i));
            }
            __syncthreads();
            if (cta < 128) {
                if (tid < 128) ((float4*)g_O)[cta * 128 + tid] = make_float4(0.f, 0.f, 0.f, 0.f);
            } else if (cta == 128) {
                for (int k = tid; k < NB * DM / 4; k += 256) ((float4*)g_h)[k] = make_float4(0.f, 0.f, 0.f, 0.f);
            } else if (cta == 129) {
                if (tid < 201) g_cnt[tid * CPAD] = 0u;
            }
            if (cta < 128) {
                float v[14];
#pragma unroll
                for (int i = 0; i < 7; i++) {
                    v[2 * i] = bf_lo(xw[i]);
                    v[2 * i + 1] = bf_hi(xw[i]);
                }
                float shift = __shfl_sync(0xffffffffu, v[0], 0);
                float m, den;
                ln_stats(v, shift, m, den);
#pragma unroll
                for (int i = 0; i < 7; i++) {
                    float2 o = make_float2(ln_apply(v[2 * i], m, den), ln_apply(v[2 * i + 1], m, den));
                    *(float2*)(s_xn + warp * DM + 2 * (lane + 32 * i)) = o;
                }
                bar_sync(1, 256);
            }
            if (cta < 128) {
                float acc[8][8];
#pragma unroll
                for (int b = 0; b < 8; b++)
#pragma unroll
                    for (int e = 0; e < 8; e++) acc[b][e] = 0.f;
#pragma unroll
                for (int i = 0; i < 7; i++) {
                    float w[8];
                    w[0] = bf_lo(wv[i].x); w[1] = bf_hi(wv[i].x);
                    w[2] = bf_lo(wv[i].y); w[3] = bf_hi(wv[i].y);
                    w[4] = bf_lo(wv[i].z); w[5] = bf_hi(wv[i].z);
                    w[6] = bf_lo(wv[i].w); w[7] = bf_hi(wv[i].w);
#pragma unroll
                    for (int b = 0; b < 8; b++) {
                        float xv = s_xn[b * DM + r0 + 64 * i];
#pragma unroll
                        for (int e = 0; e < 8; e++) acc[b][e] = fmaf(xv, w[e], acc[b][e]);
                    }
                }
                const bool h4 = lane & 16, h3 = lane & 8, h2 = lane & 4;
                float a1[4][8], a2[2][8], a3[8];
#pragma unroll
                for (int b = 0; b < 4; b++)
#pragma unroll
                    for (int e = 0; e < 8; e++) {
                        float snd = h4 ? acc[b][e] : acc[b + 4][e];
                        float kp = h4 ? acc[b + 4][e] : acc[b][e];
                        a1[b][e] = kp + __shfl_xor_sync(0xffffffffu, snd, 16);
                    }
#pragma unroll
                for (int b = 0; b < 2; b++)
#pragma unroll
                    for (int e = 0; e < 8; e++) {
                        float snd = h3 ? a1[b][e] : a1[b + 2][e];
                        float kp = h3 ? a1[b + 2][e] : a1[b][e];
                        a2[b][e] = kp + __shfl_xor_sync(0xffffffffu, snd, 8);
                    }
#pragma unroll
                for (int e = 0; e < 8; e++) {
                    float snd = h2 ? a2[0][e] : a2[1][e];
                    float kp = h2 ? a2[1][e] : a2[0][e];
                    a3[e] = kp + __shfl_xor_sync(0xffffffffu, snd, 4);
                }
                const int bb = (h4 ? 4 : 0) + (h3 ? 2 : 0) + (h2 ? 1 : 0);
                float* dst = s_red + (warp * 8 + bb) * 32 + c * 8;
                *(float4*)dst = make_float4(a3[0], a3[1], a3[2], a3[3]);
                *(float4*)(dst + 4) = make_float4(a3[4], a3[5], a3[6], a3[7]);
                bar_sync(1, 256);
                float sum = 0.f;
#pragma unroll
                for (int w = 0; w < 8; w++) sum += s_red[w * 256 + tid];
                g_q[(tid >> 5) * 4096 + cta * 32 + (tid & 31)] = __float2bfloat16_rn(sum);
            }
            asm volatile("fence.proxy.async.shared::cta;" ::: "memory");
            bar_sync(1, 256);
            if (tid == 0) {
                __threadfence();
                red_add_gpu(g_qready, 1u);
            }
        }

        if (warp < 4) {
            const int w = warp;
            const int r = lane & 7, mi = lane >> 3;
            const int g = lane >> 2, t = lane & 3;
            const bool diag = (t == (g >> 1));
            const uint32_t selLo = diag ? ((g & 1) ? 0x1044u : 0x4410u) : 0x4444u;
            const uint32_t selHi = diag ? ((g & 1) ? 0x3244u : 0x4432u) : 0x4444u;
            const uint32_t offA = (mi & 1) * 512 + (mi >> 1) * 128;
            const uint32_t offBK = (16 * w + r) * 512 + mi * 128;
            const uint32_t offBV = (8 * (mi & 1) + r) * 512 + w * 128;
            float* Odst = g_O + (size_t)(cta % NREP) * NPAIR * 512 + (t & 1) * 256 + w * 64 + g * 8 + (t >> 1) * 4;
            int s = 0, ph = 0;
            while (true) {
                mbar_wait(smem_u32(&s_fullT[s]), ph);
                const int u = s_unit[s];
                if (u >= 0) {
                    mbar_wait(smem_u32(&s_fullA[s]), ph);
                    const uint32_t tile = sm_tiles + s * TILE_BYTES;
                    const uint32_t aux = sm_aux + s * AUX_BYTES;
                    if (u < NHALF) {
                        float acc[2][2][4];
#pragma unroll
                        for (int a = 0; a < 2; a++)
#pragma unroll
                            for (int b = 0; b < 2; b++)
#pragma unroll
                                for (int e = 0; e < 4; e++) acc[a][b][e] = 0.f;
#pragma unroll
                        for (int a = 0; a < 8; a++) {
                            const uint32_t rot = ((a + r) & 7) << 4;
                            uint32_t qa0[4], qa1[4], kb0[4], kb1[4];
                            ldsm4(qa0, aux + offA + rot);
                            ldsm4(qa1, aux + offA + 256 + rot);
                            ldsm4(kb0, tile + offBK + rot);
                            ldsm4(kb1, tile + offBK + 8 * 512 + rot);
                            mma16816(acc[0][0], qa0, kb0[0], kb0[1]);
                            mma16816(acc[0][1], qa1, kb0[2], kb0[3]);
                            mma16816(acc[1][0], qa0, kb1[0], kb1[1]);
                            mma16816(acc[1][1], qa1, kb1[2], kb1[3]);
                        }
                        if (diag) {
                            float v[4];
#pragma unroll
                            for (int nt = 0; nt < 2; nt++) {
                                float c0 = acc[nt][0][0] + acc[nt][1][0], c1 = acc[nt][0][1] + acc[nt][1][1];
                                float c2 = acc[nt][0][2] + acc[nt][1][2], c3 = acc[nt][0][3] + acc[nt][1][3];
                                v[2 * nt] = bf16r((g & 1) ? c1 : c0) * 0.0625f;
                                v[2 * nt + 1] = bf16r((g & 1) ? c3 : c2) * 0.0625f;
                            }
                            uint2 o = make_uint2(pack_bf16(v[0], v[1]), pack_bf16(v[2], v[3]));
                            *(uint2*)((char*)g_S + (size_t)u * 256 + g * 32 + w * 8) = o;
                        }
                    } else {
                        uint32_t pk[8];
                        asm volatile("ld.shared.v4.u32 {%0,%1,%2,%3}, [%4];"
                                     : "=r"(pk[0]), "=r"(pk[1]), "=r"(pk[2]), "=r"(pk[3])
                                     : "r"(aux + g * 32)
                                     : "memory");
                        asm volatile("ld.shared.v4.u32 {%0,%1,%2,%3}, [%4];"
                                     : "=r"(pk[4]), "=r"(pk[5]), "=r"(pk[6]), "=r"(pk[7])
                                     : "r"(aux + g * 32 + 16)
                                     : "memory");
                        float acc[8][4];
#pragma unroll
                        for (int a = 0; a < 8; a++)
#pragma unroll
                            for (int e = 0; e < 4; e++) acc[a][e] = 0.f;
#pragma unroll
                        for (int k = 0; k < 4; k++) {
                            uint32_t pa[4];
                            pa[0] = __byte_perm(pk[2 * k], 0u, selLo);
                            pa[1] = __byte_perm(pk[2 * k], 0u, selHi);
                            pa[2] = __byte_perm(pk[2 * k + 1], 0u, selLo);
                            pa[3] = __byte_perm(pk[2 * k + 1], 0u, selHi);
#pragma unroll
                            for (int cp = 0; cp < 4; cp++) {
                                const uint32_t rot = ((2 * cp + (mi >> 1) + r) & 7) << 4;
                                uint32_t vb[4];
                                ldsm4t(vb, tile + offBV + k * 16 * 512 + rot);
                                mma16816(acc[2 * cp], pa, vb[0], vb[1]);
                                mma16816(acc[2 * cp + 1], pa, vb[2], vb[3]);
                            }
                        }
                        const int l4 = (((g - 4) & 7) << 2) | t, l2 = (((g - 2) & 7) << 2) | t, l1 = (((g - 1) & 7) << 2) | t;
#pragma unroll
                        for (int c = 0; c < 4; c++)
#pragma unroll
                            for (int e = 0; e < 4; e++) acc[c][e] += __shfl_sync(0xffffffffu, acc[c + 4][e], l4);
#pragma unroll
                        for (int c = 0; c < 2; c++)
#pragma unroll
                            for (int e = 0; e < 4; e++) acc[c][e] += __shfl_sync(0xffffffffu, acc[c + 2][e], l2);
#pragma unroll
                        for (int e = 0; e < 4; e++) acc[0][e] += __shfl_sync(0xffffffffu, acc[1][e], l1);
                        const bool odd = t & 1;
                        float sx = odd ? acc[0][0] : acc[0][2], sy = odd ? acc[0][1] : acc[0][3];
                        float rx = __shfl_xor_sync(0xffffffffu, sx, 1), ry = __shfl_xor_sync(0xffffffffu, sy, 1);
                        float* dst = Odst + (size_t)((u - NHALF) / UPP) * 512;
                        if (odd) red_add_v4(dst, rx, ry, acc[0][2], acc[0][3]);
                        else red_add_v4(dst, acc[0][0], acc[0][1], rx, ry);
                    }
                }
                __syncwarp();
                if (lane == 0) {
                    int old = atom_add_acqrel_cta_s(smem_u32(&s_cnt[s]), 1);
                    if (old == 3) {
                        s_cnt[s] = 0;
                        int slot = atom_add_acqrel_cta_s(smem_u32(&s_fifo_head), 1) % FIFO_N;
                        long long t0 = clock64();
                        while (ld_acquire_cta_s(smem_u32(&s_fifo[slot])) != EMPTY) {
                            if (clock64() - t0 > SPIN_LIMIT) __trap();
                        }
                        st_release_cta_s(smem_u32(&s_fifo[slot]), u);
                    }
                    mbar_arrive(smem_u32(&s_empty[s]));
                }
                if (u < 0) break;
                if (++s == RING) { s = 0; ph ^= 1; }
            }
        } else {
            const int at = tid - 128, aw = warp - 4;
            const unsigned char* mlp_s = wo_s + WO_BYTES;
            if (at == 0 && cta < 128) {
                mbar_expect_tx(smem_u32(&s_wobar), WO_BYTES + 3 * MLPW_BYTES);
                bulk_load_nohint(smem_u32(wo_s), (const char*)prm.wo + (size_t)cta * WO_BYTES, WO_BYTES, smem_u32(&s_wobar));
                bulk_load_nohint(smem_u32(mlp_s), prm.w1, MLPW_BYTES, smem_u32(&s_wobar));
                bulk_load_nohint(smem_u32(mlp_s + MLPW_BYTES), prm.b1, MLPW_BYTES, smem_u32(&s_wobar));
                bulk_load_nohint(smem_u32(mlp_s + 2 * MLPW_BYTES), prm.w2, MLPW_BYTES, smem_u32(&s_wobar));
            }
            const float b2v = __bfloat162float(prm.b2[0]);
            int step = 0, ljt = 0, flip = 0;
            const int nsteps = (cta < 128) ? 16 : 0;
            bool wo_ready = false;
            while (true) {
                if (at == 0) {
                    int job;
                    long long t0 = clock64();
                    while (true) {
                        int sd = ld_acquire_cta_s(smem_u32(&s_sigdone));
                        int lj = (ljt < 64) ? ld_acquire_cta_s(smem_u32(&s_lj[ljt])) : EMPTY;
                        if (lj != EMPTY) { job = lj; break; }
                        if (step < nsteps && (step & 1) && cta >= 112) { step++; continue; }
                        if (step >= nsteps) {
                            if (sd) { job = 1000; break; }
                            __nanosleep(100);
                        } else if (*(volatile int*)&s_phase2) {
                            const int b = step >> 1;
                            if (!(step & 1)) {
                                if (ld_acquire_gpu(cntV(b * 8 + (cta >> 4))) >= (unsigned)UPP) { job = 100 + step; break; }
                            } else {
                                if (ld_acquire_gpu(cntH(b)) >= 128u) { job = 100 + step; break; }
                            }
                        } else {
                            __nanosleep(100);
                        }
                        if (clock64() - t0 > SPIN_LIMIT) __trap();
                    }
                    s_job[flip] = job;
                }
                bar_sync(2, 128);
                const int job = s_job[flip];
                flip ^= 1;
                if (job == 1000) break;
                if (job < 100) {
                    ljt++;
                    uint4* Sp = g_S + (size_t)job * 2048 + at;
                    uint4 v[16];
#pragma unroll
                    for (int n = 0; n < 16; n++) v[n] = __ldcg(Sp + 128 * n);
                    uint32_t mx = v[0].x;
#pragma unroll
                    for (int n = 0; n < 16; n++) {
                        mx = hmax2_bf16(mx, hmax2_bf16(hmax2_bf16(v[n].x, v[n].y), hmax2_bf16(v[n].z, v[n].w)));
                    }
#pragma unroll
                    for (int o = 16; o > 0; o >>= 1) mx = hmax2_bf16(mx, __shfl_xor_sync(0xffffffffu, mx, o));
                    if (lane == 0) s_redu[aw] = mx;
                    bar_sync(2, 128);
                    mx = hmax2_bf16(hmax2_bf16(s_redu[0], s_redu[1]), hmax2_bf16(s_redu[2], s_redu[3]));
                    const float L2E = 1.4426950408889634f;
                    const float m0 = bf_lo(mx), m1 = bf_hi(mx);
                    float s0 = 0.f, s1 = 0.f;
#pragma unroll
                    for (int n = 0; n < 16; n++) {
                        uint32_t ww[4] = {v[n].x, v[n].y, v[n].z, v[n].w};
#pragma unroll
                        for (int k = 0; k < 4; k++) {
                            s0 += ex2f((bf_lo(ww[k]) - m0) * L2E);
                            s1 += ex2f((bf_hi(ww[k]) - m1) * L2E);
                        }
                    }
                    s0 = warp_sum(s0);
                    s1 = warp_sum(s1);
                    if (lane == 0) { s_redf[aw] = s0; s_redf[4 + aw] = s1; }
                    bar_sync(2, 128);
                    const float i0 = __fdiv_rn(1.0f, (s_redf[0] + s_redf[1]) + (s_redf[2] + s_redf[3]));
                    const float i1 = __fdiv_rn(1.0f, (s_redf[4] + s_redf[5]) + (s_redf[6] + s_redf[7]));
#pragma unroll
                    for (int n = 0; n < 16; n++) {
                        uint32_t ww[4] = {v[n].x, v[n].y, v[n].z, v[n].w};
#pragma unroll
                        for (int k = 0; k < 4; k++) {
                            float p0 = ex2f((bf_lo(ww[k]) - m0) * L2E) * i0;
                            float p1 = ex2f((bf_hi(ww[k]) - m1) * L2E) * i1;
                            ww[k] = pack_bf16(p0, p1);
                        }
                        __stcg(Sp + 128 * n, make_uint4(ww[0], ww[1], ww[2], ww[3]));
                    }
                    bar_sync(2, 128);
                    if (at == 0) {
                        __threadfence();
                        red_add_gpu(flagP(job), 1u);
                        red_add_gpu(cntL(), 1u);
                    }
                } else if (!((job - 100) & 1)) {
                    const int b = (job - 100) >> 1;
                    step = job - 100 + 1;
                    if (at < 32) {
                        const float* src = g_O + (size_t)(b * 8 + (cta >> 4)) * 512 + (cta & 15) * 32 + at;
                        float o = 0.f;
#pragma unroll
                        for (int rp = 0; rp < NREP; rp++) o += __ldcg(src + (size_t)rp * NPAIR * 512);
                        s_o[at] = bf16r(o);
                    }
                    if (!wo_ready) { mbar_wait(smem_u32(&s_wobar), 0); wo_ready = true; }
                    bar_sync(2, 128);
                    if (at < 112) {
                        float a0 = 0.f, a1 = 0.f, a2 = 0.f, a3 = 0.f;
#pragma unroll
                        for (int i = 0; i < 32; i++) {
                            uint2 wv = *(const uint2*)(wo_s + i * (DM * 2) + at * 8);
                            float ov = s_o[i];
                            a0 = fmaf(ov, bf_lo(wv.x), a0);
                            a1 = fmaf(ov, bf_hi(wv.x), a1);
                            a2 = fmaf(ov, bf_lo(wv.y), a2);
                            a3 = fmaf(ov, bf_hi(wv.y), a3);
                        }
                        red_add_v4(g_h + b * DM + at * 4, a0, a1, a2, a3);
                    }
                    bar_sync(2, 128);
                    if (at == 0) {
                        __threadfence();
                        red_add_gpu(cntH(b), 1u);
                    }
                } else {
                    const int b = (job - 100) >> 1;
                    step = job - 100 + 1;
                    const int col = cta * 4 + aw;
                    const float2* hp = (const float2*)(g_h + b * DM);
                    const uint32_t* xr = (const uint32_t*)(prm.x + b * DM);
                    float v[14];
                    float hc_a = __ldcg(g_h + b * DM + col);
                    float hc_x = __bfloat162float(prm.x[b * DM + col]);
#pragma unroll
                    for (int i = 0; i < 7; i++) {
                        float2 a = __ldcg(hp + lane + 32 * i);
                        uint32_t xw = __ldg(xr + lane + 32 * i);
                        v[2 * i] = bf16r(bf_lo(xw) + bf16r(a.x));
                        v[2 * i + 1] = bf16r(bf_hi(xw) + bf16r(a.y));
                    }
                    const float hc = bf16r(hc_x + bf16r(hc_a));
                    float m1, d1, m2, d2;
                    ln_stats(v, hc, m1, d1);
#pragma unroll
                    for (int i = 0; i < 14; i++) v[i] = ln_apply(v[i], m1, d1);
                    ln_stats(v, 0.f, m2, d2);
                    const float yc = ln_apply(ln_apply(hc, m1, d1), m2, d2);
                    const uint32_t hh = pack_bf16(yc, yc);
                    const float K0 = 0.7978845608028654f, K01 = 0.7978845608028654f * 0.044715f;
                    float acc0 = 0.f, acc1 = 0.f;
#pragma unroll
                    for (int i = 0; i < 7; i++) {
                        const uint4 w1v = *(const uint4*)(mlp_s + (lane + 32 * i) * 16);
                        const uint4 b1v = *(const uint4*)(mlp_s + MLPW_BYTES + (lane + 32 * i) * 16);
                        const uint4 w2v = *(const uint4*)(mlp_s + 2 * MLPW_BYTES + (lane + 32 * i) * 16);
                        const uint32_t w1p[4] = {w1v.x, w1v.y, w1v.z, w1v.w};
                        const uint32_t b1p[4] = {b1v.x, b1v.y, b1v.z, b1v.w};
                        const uint32_t w2p[4] = {w2v.x, w2v.y, w2v.z, w2v.w};
#pragma unroll
                        for (int k = 0; k < 4; k++) {
                            uint32_t u2 = hadd2_bf16(hmul2_bf16(hh, w1p[k]), b1p[k]);
                            float ua = bf_lo(u2), ub = bf_hi(u2);
                            float za = ua * fmaf(ua * ua, K01, K0), zb = ub * fmaf(ub * ub, K01, K0);
                            float ga = fmaf(ua, tanh_fast(za), ua), gb = fmaf(ub, tanh_fast(zb), ub);
                            uint32_t gp = pack_bf16(ga, gb);
                            acc0 = fmaf(bf_lo(gp), bf_lo(w2p[k]), acc0);
                            acc1 = fmaf(bf_hi(gp), bf_hi(w2p[k]), acc1);
                        }
                    }
                    float y = 0.5f * warp_sum(acc0 + acc1);
                    if (lane == 0) {
                        float y2 = bf16r(bf16r(y) + b2v);
                        prm.out[b * DM + col] = __float2bfloat16_rn(hc + y2);
                    }
                }
            }
        }
    }
    __syncthreads();
    if (tid == 0) {
        unsigned old = atomicAdd(g_exit, 1u);
        if (old == (unsigned)(G - 1)) {
            g_work[0] = 0u;
            g_qready[0] = 0u;
            g_exit[0] = 0u;
            __threadfence();
        }
    }
}

}

extern "C" void kernel_launch(void* const* d_in, const int* in_sizes, int n_in, void* d_out, int out_size) {
    (void)in_sizes; (void)n_in; (void)out_size;
    static int grid = 0;
    if (grid == 0) {
        int dev = 0, sms = 0;
        cudaGetDevice(&dev);
        cudaDeviceGetAttribute(&sms, cudaDevAttrMultiProcessorCount, dev);
        cudaFuncSetAttribute(fused_decode_kernel, cudaFuncAttributeMaxDynamicSharedMemorySize, SMEM_BYTES);
        grid = sms < 132 ? sms : 132;
    }
    Params p;
    p.x = (const __nv_bfloat16*)d_in[0];
    p.K = (const char*)d_in[1];
    p.V = (const char*)d_in[2];
    p.wq = (const __nv_bfloat16*)d_in[3];
    p.wo = (const __nv_bfloat16*)d_in[4];
    p.w1 = (const __nv_bfloat16*)d_in[6];
    p.b1 = (const __nv_bfloat16*)d_in[7];
    p.w2 = (const __nv_bfloat16*)d_in[8];
    p.b2 = (const __nv_bfloat16*)d_in[9];
    p.out = (__nv_bfloat16*)d_out;
    fused_decode_kernel<<<grid, NTHREADS, SMEM_BYTES>>>(p);
}
```

```cpp
#include <cuda_runtime.h>
#include <cuda_bf16.h>
#include <stdint.h>

namespace {

constexpr int NB = 8, DM = 448, SK = 8192, DH = 256, FF = 1792;
constexpr int NPAIR = 64;
constexpr int UNIT_KEYS = 64;
constexpr int UPP = SK / UNIT_KEYS;
constexpr int NHALF = NPAIR * UPP;
constexpr int NUNITS = 2 * NHALF;
constexpr int TILE_BYTES = UNIT_KEYS * DH * 2;
constexpr int AUX_BYTES = 1024;
constexpr int RING = 5;
constexpr int PF = 1;
constexpr int NSUB = 2;
constexpr int CHUNK = TILE_BYTES / NSUB;
constexpr int LIM = 3;
constexpr int NREP = 4;
constexpr int P_SLEEP = 400;
constexpr int WO_BYTES = 512 * 64;
constexpr int MLPW_BYTES = FF * 2;
constexpr int X_BYTES = NB * DM * 2;
constexpr int SMEM_BYTES = RING * (TILE_BYTES + AUX_BYTES) + WO_BYTES + 3 * MLPW_BYTES + X_BYTES;
constexpr int NTHREADS = 512;
constexpr int FIFO_N = 32;
constexpr int CPAD = 32;
constexpr int EMPTY = -2, SENTINEL = -1;
constexpr int SIG_P = 30000;
constexpr int OVEC = 192;
constexpr int HVEC = DM / 2;

__device__ __align__(1024) uint2 g_q[NB * 2048];
__device__ __align__(1024) uint32_t g_qp[NB * 2048];
__device__ __align__(1024) uint4 g_S[NPAIR * 2048];
__device__ __align__(1024) float4 g_O[NREP * NPAIR * OVEC];
__device__ __align__(1024) float4 g_h[NB * HVEC];
__device__ __align__(1024) unsigned g_cnt[(64 * 2 + 1) * CPAD];
__device__ __align__(128) unsigned g_work[CPAD];
__device__ __align__(128) unsigned g_qready[CPAD];
__device__ __align__(128) unsigned long long g_ticket[CPAD / 2];

__device__ __forceinline__ unsigned* cntK(int p) { return g_cnt + (p)*CPAD; }
__device__ __forceinline__ unsigned* flagP(int p) { return g_cnt + (64 + p) * CPAD; }
__device__ __forceinline__ unsigned* cntL() { return g_cnt + (128) * CPAD; }

__device__ __forceinline__ uint32_t smem_u32(const void* p) { return (uint32_t)__cvta_generic_to_shared(p); }
__device__ __forceinline__ void mbar_init(uint32_t bar, uint32_t cnt) {
    asm volatile("mbarrier.init.shared::cta.b64 [%0], %1;" ::"r"(bar), "r"(cnt) : "memory");
}
__device__ __forceinline__ void mbar_expect_tx(uint32_t bar, uint32_t bytes) {
    asm volatile("mbarrier.arrive.expect_tx.shared::cta.b64 _, [%0], %1;" ::"r"(bar), "r"(bytes) : "memory");
}
__device__ __forceinline__ void mbar_arrive(uint32_t bar) {
    asm volatile("mbarrier.arrive.shared::cta.b64 _, [%0];" ::"r"(bar) : "memory");
}
__device__ __forceinline__ bool mbar_try(uint32_t bar, uint32_t parity) {
    uint32_t done;
    asm volatile(
        "{\n.reg .pred p;\nmbarrier.try_wait.parity.shared::cta.b64 p, [%1], %2;\nselp.u32 %0, 1, 0, p;\n}"
        : "=r"(done)
        : "r"(bar), "r"(parity)
        : "memory");
    return done != 0;
}
constexpr long long SPIN_LIMIT = 4000000000LL;
__device__ __forceinline__ void mbar_wait(uint32_t bar, uint32_t parity) {
    if (mbar_try(bar, parity)) return;
    long long t0 = clock64();
    while (!mbar_try(bar, parity)) {
        if (clock64() - t0 > SPIN_LIMIT) __trap();
    }
}
__device__ __forceinline__ void bulk_load(uint32_t dst, const void* src, uint32_t bytes, uint32_t bar, uint64_t pol) {
    asm volatile(
        "cp.async.bulk.shared::cluster.global.mbarrier::complete_tx::bytes.L2::cache_hint [%0], [%1], %2, [%3], %4;" ::"r"(dst),
        "l"(src), "r"(bytes), "r"(bar), "l"(pol)
        : "memory");
}
__device__ __forceinline__ void bulk_load_nohint(uint32_t dst, const void* src, uint32_t bytes, uint32_t bar) {
    asm volatile("cp.async.bulk.shared::cluster.global.mbarrier::complete_tx::bytes [%0], [%1], %2, [%3];" ::"r"(dst),
                 "l"(src), "r"(bytes), "r"(bar)
                 : "memory");
}
__device__ __forceinline__ void cp_async16(uint32_t dst, const void* src) {
    asm volatile("cp.async.cg.shared.global [%0], [%1], 16;" ::"r"(dst), "l"(src) : "memory");
}
__device__ __forceinline__ void cp_async_arrive_noinc(uint32_t bar) {
    asm volatile("cp.async.mbarrier.arrive.noinc.shared::cta.b64 [%0];" ::"r"(bar) : "memory");
}
__device__ __forceinline__ unsigned ld_acquire_gpu(const unsigned* p) {
    unsigned v;
    asm volatile("ld.acquire.gpu.global.u32 %0, [%1];" : "=r"(v) : "l"(p) : "memory");
    return v;
}
__device__ __forceinline__ void red_add_gpu(unsigned* p, unsigned v) {
    asm volatile("red.relaxed.gpu.global.add.u32 [%0], %1;" ::"l"(p), "r"(v) : "memory");
}
__device__ __forceinline__ unsigned atom_add_relaxed_gpu(unsigned* p, unsigned v) {
    unsigned o;
    asm volatile("atom.relaxed.gpu.global.add.u32 %0, [%1], %2;" : "=r"(o) : "l"(p), "r"(v) : "memory");
    return o;
}
__device__ __forceinline__ void red_add_v4(float* p, float a, float b, float c, float d) {
    asm volatile("red.relaxed.gpu.global.add.v4.f32 [%0], {%1,%2,%3,%4};" ::"l"(p), "f"(a), "f"(b), "f"(c), "f"(d) : "memory");
}
__device__ __forceinline__ float4 ld_relaxed_v4(const float4* p) {
    float4 v;
    asm volatile("ld.relaxed.gpu.global.v4.f32 {%0,%1,%2,%3}, [%4];" : "=f"(v.x), "=f"(v.y), "=f"(v.z), "=f"(v.w) : "l"(p) : "memory");
    return v;
}
__device__ __forceinline__ void ld_relaxed_2x64(const void* p, unsigned long long& a, unsigned long long& b) {
    asm volatile("ld.relaxed.gpu.global.v2.b64 {%0,%1}, [%2];" : "=l"(a), "=l"(b) : "l"(p) : "memory");
}
__device__ __forceinline__ void st_relaxed_64(void* p, unsigned long long v) {
    asm volatile("st.relaxed.gpu.global.b64 [%0], %1;" ::"l"(p), "l"(v) : "memory");
}
__device__ __forceinline__ void wait_counter(const unsigned* p, unsigned target) {
    if ((int)(ld_acquire_gpu(p) - target) >= 0) return;
    long long t0 = clock64();
    while ((int)(ld_acquire_gpu(p) - target) < 0) {
        __nanosleep(100);
        if (clock64() - t0 > SPIN_LIMIT) __trap();
    }
}
__device__ __forceinline__ int ld_acquire_cta_s(uint32_t a) {
    int v;
    asm volatile("ld.acquire.cta.shared::cta.s32 %0, [%1];" : "=r"(v) : "r"(a) : "memory");
    return v;
}
__device__ __forceinline__ void st_release_cta_s(uint32_t a, int v) {
    asm volatile("st.release.cta.shared::cta.s32 [%0], %1;" ::"r"(a), "r"(v) : "memory");
}
__device__ __forceinline__ int atom_add_acqrel_cta_s(uint32_t a, int v) {
    int o;
    asm volatile("atom.acq_rel.cta.shared::cta.add.s32 %0, [%1], %2;" : "=r"(o) : "r"(a), "r"(v) : "memory");
    return o;
}
__device__ __forceinline__ void bar_sync(int id, int n) { asm volatile("bar.sync %0, %1;" ::"r"(id), "r"(n) : "memory"); }
__device__ __forceinline__ bool bar_red_and(int id, int n, bool p) {
    uint32_t r;
    asm volatile(
        "{\n.reg .pred p, q;\nsetp.ne.u32 p, %3, 0;\nbarrier.cta.red.and.aligned.pred q, %1, %2, p;\nselp.u32 %0, 1, 0, q;\n}"
        : "=r"(r)
        : "r"(id), "r"(n), "r"((uint32_t)p)
        : "memory");
    return r != 0;
}
__device__ __forceinline__ void ldsm4(uint32_t (&r)[4], uint32_t addr) {
    asm volatile("ldmatrix.sync.aligned.m8n8.x4.shared.b16 {%0,%1,%2,%3}, [%4];"
                 : "=r"(r[0]), "=r"(r[1]), "=r"(r[2]), "=r"(r[3])
                 : "r"(addr)
                 : "memory");
}
__device__ __forceinline__ void ldsm4t(uint32_t (&r)[4], uint32_t addr) {
    asm volatile("ldmatrix.sync.aligned.m8n8.x4.trans.shared.b16 {%0,%1,%2,%3}, [%4];"
                 : "=r"(r[0]), "=r"(r[1]), "=r"(r[2]), "=r"(r[3])
                 : "r"(addr)
                 : "memory");
}
__device__ __forceinline__ void mma16816(float (&c)[4], const uint32_t (&a)[4], uint32_t b0, uint32_t b1) {
    asm volatile(
        "mma.sync.aligned.m16n8k16.row.col.f32.bf16.bf16.f32 {%0,%1,%2,%3}, {%4,%5,%6,%7}, {%8,%9}, {%0,%1,%2,%3};"
        : "+f"(c[0]), "+f"(c[1]), "+f"(c[2]), "+f"(c[3])
        : "r"(a[0]), "r"(a[1]), "r"(a[2]), "r"(a[3]), "r"(b0), "r"(b1));
}
__device__ __forceinline__ float bf16r(float x) { return __bfloat162float(__float2bfloat16_rn(x)); }
__device__ __forceinline__ float bf_lo(uint32_t w) { return __uint_as_float(w << 16); }
__device__ __forceinline__ float bf_hi(uint32_t w) { return __uint_as_float(w & 0xffff0000u); }
__device__ __forceinline__ uint32_t pack_bf16(float lo, float hi) {
    uint32_t r;
    asm("cvt.rn.bf16x2.f32 %0, %1, %2;" : "=r"(r) : "f"(hi), "f"(lo));
    return r;
}
__device__ __forceinline__ float ex2f(float x) {
    float y;
    asm("ex2.approx.ftz.f32 %0, %1;" : "=f"(y) : "f"(x));
    return y;
}
__device__ __forceinline__ float sqrt_fast(float x) {
    float y;
    asm("sqrt.approx.f32 %0, %1;" : "=f"(y) : "f"(x));
    return y;
}
__device__ __forceinline__ float rcp_fast(float x) {
    float y;
    asm("rcp.approx.f32 %0, %1;" : "=f"(y) : "f"(x));
    return y;
}
__device__ __forceinline__ float tanh_fast(float x) {
    float y;
    asm("tanh.approx.f32 %0, %1;" : "=f"(y) : "f"(x));
    return y;
}
__device__ __forceinline__ uint32_t hmax2_bf16(uint32_t a, uint32_t b) {
    uint32_t r;
    asm("max.bf16x2 %0, %1, %2;" : "=r"(r) : "r"(a), "r"(b));
    return r;
}
__device__ __forceinline__ uint32_t hmul2_bf16(uint32_t a, uint32_t b) {
    uint32_t r;
    asm("mul.rn.bf16x2 %0, %1, %2;" : "=r"(r) : "r"(a), "r"(b));
    return r;
}
__device__ __forceinline__ uint32_t hadd2_bf16(uint32_t a, uint32_t b) {
    uint32_t r;
    asm("add.rn.bf16x2 %0, %1, %2;" : "=r"(r) : "r"(a), "r"(b));
    return r;
}
__device__ __forceinline__ float warp_sum(float v) {
#pragma unroll
    for (int o = 16; o > 0; o >>= 1) v += __shfl_xor_sync(0xffffffffu, v, o);
    return v;
}

__device__ __forceinline__ void ln_stats(const float (&v)[14], float shift, float& m, float& den) {
    float s1 = 0.f, s2 = 0.f;
#pragma unroll
    for (int i = 0; i < 14; i++) {
        float d = v[i] - shift;
        s1 += d;
        s2 = fmaf(d, d, s2);
    }
#pragma unroll
    for (int o = 16; o > 0; o >>= 1) {
        s1 += __shfl_xor_sync(0xffffffffu, s1, o);
        s2 += __shfl_xor_sync(0xffffffffu, s2, o);
    }
    const float inv = 1.0f / (float)DM;
    float md = s1 * inv;
    float var = fmaxf(s2 * inv - md * md, 0.f);
    m = bf16r(shift + md);
    den = rcp_fast(bf16r(sqrt_fast(bf16r(bf16r(var) + 1e-5f))));
}
__device__ __forceinline__ float ln_apply(float x, float m, float rden) { return bf16r(bf16r(x - m) * rden); }

__device__ __forceinline__ void ln_stats_block(const float (&v)[4], int aw, int lane, float* scr, float& m, float& rden) {
    float mean = 0.25f * ((v[0] + v[1]) + (v[2] + v[3]));
    float e0 = v[0] - mean, e1 = v[1] - mean, e2 = v[2] - mean, e3 = v[3] - mean;
    float m2 = fmaf(e0, e0, e1 * e1) + fmaf(e2, e2, e3 * e3);
    float half_n = 2.0f;
#pragma unroll
    for (int o = 1; o < 32; o <<= 1) {
        float mo = __shfl_xor_sync(0xffffffffu, mean, o), qo = __shfl_xor_sync(0xffffffffu, m2, o);
        if (o < 16 || aw < 3) {
            float d = mo - mean;
            m2 = fmaf(d * d, half_n, m2 + qo);
            mean = 0.5f * (mean + mo);
        }
        half_n *= 2.0f;
    }
    if (lane == 0) *(float2*)(scr + 2 * aw) = make_float2(mean, m2);
    bar_sync(2, 128);
    const float4 a = *(const float4*)scr, b = *(const float4*)(scr + 4);
    const float mu = (128.f * (a.x + a.z + b.x) + 64.f * b.z) * (1.0f / 448.f);
    const float d0 = a.x - mu, d1 = a.z - mu, d2 = b.x - mu, d3 = b.z - mu;
    const float M2 = (a.y + a.w) + (b.y + b.w) + 128.f * (d0 * d0 + d1 * d1 + d2 * d2) + 64.f * d3 * d3;
    m = bf16r(mu);
    rden = rcp_fast(bf16r(sqrt_fast(bf16r(bf16r(M2 * (1.0f / 448.f)) + 1e-5f))));
}

__device__ __forceinline__ void fifo_push(int* fifo, int* head, int v) {
    int slot = atom_add_acqrel_cta_s(smem_u32(head), 1) % FIFO_N;
    if (ld_acquire_cta_s(smem_u32(&fifo[slot])) != EMPTY) {
        long long t0 = clock64();
        while (ld_acquire_cta_s(smem_u32(&fifo[slot])) != EMPTY) {
            if (clock64() - t0 > SPIN_LIMIT) __trap();
        }
    }
    st_release_cta_s(smem_u32(&fifo[slot]), v);
}

struct Params {
    const __nv_bfloat16* x;
    const char* K;
    const char* V;
    const __nv_bfloat16* wq;
    const __nv_bfloat16* wo;
    const __nv_bfloat16* w1;
    const __nv_bfloat16* b1;
    const __nv_bfloat16* w2;
    const __nv_bfloat16* b2;
    __nv_bfloat16* out;
};

__global__ void __launch_bounds__(NTHREADS, 1) fused_decode_kernel(const Params prm) {
    extern __shared__ __align__(1024) unsigned char smem[];
    __shared__ __align__(8) uint64_t s_fullT[RING][NSUB], s_fullA[RING], s_empty[RING], s_issued[RING], s_wobar, s_epbar;
    __shared__ unsigned s_epoch;
    __shared__ int s_unit[RING], s_cnt[RING];
    __shared__ int s_fifo[FIFO_N], s_fifo_head;
    __shared__ int s_phase2, s_sdone, s_qok;
    __shared__ float s_o[512];
    __shared__ __align__(8) float s_pr[4 * 32];
    __shared__ uint32_t s_redu[8];
    __shared__ __align__(16) float s_redf[8];
    __shared__ __align__(16) float s_hc[4];
    __shared__ __align__(16) float s_ln[16];

    const int tid = threadIdx.x, warp = tid >> 5, lane = tid & 31;
    const int cta = blockIdx.x, G = gridDim.x;
    const uint32_t sm_tiles = smem_u32(smem);
    const uint32_t sm_aux = sm_tiles + RING * TILE_BYTES;
    unsigned char* wo_s = smem + RING * (TILE_BYTES + AUX_BYTES);

    uint4 wv[7];
    uint32_t xw[7];
    if (warp < 8 && cta < 128) {
        uint64_t pol_ef;
        asm volatile("createpolicy.fractional.L2::evict_first.b64 %0, 1.0;" : "=l"(pol_ef));
#pragma unroll
        for (int i = 0; i < 7; i++)
            asm volatile("ld.global.nc.u32 %0, [%1];" : "=r"(xw[i]) : "l"((const uint32_t*)(prm.x + warp * DM) + lane + 32 * i));
#pragma unroll
        for (int i = 0; i < 7; i++) {
            const uint4* p = (const uint4*)(prm.wq + (size_t)((tid >> 2) + 64 * i) * 4096 + cta * 32 + (tid & 3) * 8);
            asm volatile("ld.global.nc.L1::no_allocate.L2::cache_hint.v4.u32 {%0,%1,%2,%3}, [%4], %5;"
                         : "=r"(wv[i].x), "=r"(wv[i].y), "=r"(wv[i].z), "=r"(wv[i].w)
                         : "l"(p), "l"(pol_ef));
        }
    }
    if (warp == 12) {
        bool firstV = true;
        uint64_t pol = 0;
        unsigned wq_[PF];
        int inflight = 0;
        int lc_s = 0, lc_h = 0, lc_p = 0;
        auto issue_tile = [&](int u, int s) {
            s_unit[s] = u;
            mbar_arrive(smem_u32(&s_issued[s]));
            const char* src = (u < NHALF) ? prm.K + (size_t)u * TILE_BYTES : prm.V + (size_t)(u - NHALF) * TILE_BYTES;
#pragma unroll
            for (int h = 0; h < NSUB; h++) {
                while (inflight >= LIM) {
                    mbar_wait(smem_u32(&s_fullT[lc_s][lc_h]), lc_p);
                    inflight--;
                    if (++lc_h == NSUB) { lc_h = 0; if (++lc_s == RING) { lc_s = 0; lc_p ^= 1; } }
                }
                mbar_expect_tx(smem_u32(&s_fullT[s][h]), CHUNK);
                bulk_load(sm_tiles + s * TILE_BYTES + h * CHUNK, src + h * CHUNK, CHUNK, smem_u32(&s_fullT[s][h]), pol);
                inflight++;
            }
        };
        if (lane == 0) {
            for (int s = 0; s < RING; s++) {
                for (int h = 0; h < NSUB; h++) mbar_init(smem_u32(&s_fullT[s][h]), 1);
                mbar_init(smem_u32(&s_fullA[s]), 32);
                mbar_init(smem_u32(&s_empty[s]), 4);
                mbar_init(smem_u32(&s_issued[s]), 1);
                s_cnt[s] = 0;
            }
            mbar_init(smem_u32(&s_wobar), 1);
            mbar_init(smem_u32(&s_epbar), 1);
            asm volatile("fence.mbarrier_init.release.cluster;" ::: "memory");
            asm volatile("fence.proxy.async.shared::cta;" ::: "memory");
            asm volatile("createpolicy.fractional.L2::evict_first.b64 %0, 1.0;" : "=l"(pol));
            issue_tile(cta, 0);
#pragma unroll
            for (int k = 0; k < PF; k++) wq_[k] = atom_add_relaxed_gpu(g_work, 1u);
        }
        s_fifo[lane] = EMPTY;
        if (lane == 0) { s_fifo_head = 0; s_phase2 = 0; s_sdone = 0; s_qok = 0; }
        __syncthreads();
        if (lane == 0) {
            issue_tile(cta + G, 1);
            mbar_wait(smem_u32(&s_epbar), 0);
            const unsigned wbase = s_epoch * (unsigned)(NUNITS + (PF - 2) * G) - (unsigned)(2 * G);
            int s = 2, n = 0;
            bool more = true;
            while (more) {
#pragma unroll
                for (int k = 0; k < PF; k++) {
                    if (more) {
                        const int u = (int)(wq_[k] - wbase);
                        if (u >= NUNITS) {
                            more = false;
                        } else {
                            mbar_wait(smem_u32(&s_empty[s]), (n & 1) ^ 1);
                            issue_tile(u, s);
                            wq_[k] = atom_add_relaxed_gpu(g_work, 1u);
                            if (u >= NHALF && firstV) { firstV = false; s_phase2 = 1; }
                            if (++s == RING) { s = 0; n++; }
                        }
                    }
                }
            }
            s_phase2 = 1;
#pragma unroll
            for (int k = 0; k < 2; k++) {
                mbar_wait(smem_u32(&s_empty[s]), (n & 1) ^ 1);
                s_unit[s] = SENTINEL;
                mbar_arrive(smem_u32(&s_issued[s]));
                if (++s == RING) { s = 0; n++; }
            }
        }
    } else if (warp >= 14) {
        __syncthreads();
        mbar_wait(smem_u32(&s_epbar), 0);
        const unsigned tag = s_epoch + 1u, qtarget = tag * (unsigned)G;
        bool allL = false, qall = false;
        int s = (warp - 14) % RING, n = 0;
        while (true) {
            mbar_wait(smem_u32(&s_issued[s]), n & 1);
            const int u = s_unit[s];
            if (u < 0) break;
            const uint32_t aux = sm_aux + s * AUX_BYTES;
            if (u < NHALF && !qall) {
                const char* src = (const char*)g_q + (size_t)(u / UPP) * 2048 + lane * 16;
                unsigned long long a[4], b[4];
                unsigned qr = 0;
                long long t0 = 0;
                while (true) {
                    bool ok = true;
#pragma unroll
                    for (int k = 0; k < 4; k++) ld_relaxed_2x64(src + k * 512, a[k], b[k]);
                    if (lane == 0) qr = ld_acquire_gpu(g_qready);
#pragma unroll
                    for (int k = 0; k < 4; k++) ok = ok && (unsigned)(a[k] >> 32) == tag && (unsigned)(b[k] >> 32) == tag;
                    if (__all_sync(0xffffffffu, ok)) break;
                    if (t0 == 0) t0 = clock64();
                    if (clock64() - t0 > SPIN_LIMIT) __trap();
                }
                qall = (int)(__shfl_sync(0xffffffffu, qr, 0) - qtarget) >= 0;
#pragma unroll
                for (int k = 0; k < 4; k++)
                    asm volatile("st.shared.v2.u32 [%0], {%1,%2};" ::"r"(aux + (lane + 32 * k) * 8), "r"((unsigned)a[k]), "r"((unsigned)b[k]) : "memory");
                mbar_arrive(smem_u32(&s_fullA[s]));
                if (lane == 0) *(volatile int*)&s_qok = 1;
            } else {
                if (u < NHALF) {
                    const char* src = (const char*)g_qp + (size_t)(u / UPP) * 1024;
                    cp_async16(aux + lane * 16, src + lane * 16);
                    cp_async16(aux + 512 + lane * 16, src + 512 + lane * 16);
                } else {
                    if (!allL) {
                        if (lane == 0) {
                            if (!qall) wait_counter(g_qready, qtarget);
                            if (ld_acquire_gpu(cntL()) >= (unsigned)NPAIR) allL = true;
                            else wait_counter(flagP((u - NHALF) / UPP), 1u);
                        }
                        qall = true;
                        allL = __shfl_sync(0xffffffffu, (int)allL, 0) != 0;
                    }
                    if (lane < 16) cp_async16(aux + lane * 16, (const char*)g_S + (size_t)(u - NHALF) * 256 + lane * 16);
                }
                cp_async_arrive_noinc(smem_u32(&s_fullA[s]));
            }
            s += 2;
            if (s >= RING) { s -= RING; n++; }
        }
    } else if (warp == 13) {
        unsigned long long ticket = 0;
        if (lane == 0) asm volatile("atom.relaxed.gpu.global.add.u64 %0, [%1], 1;" : "=l"(ticket) : "l"(g_ticket) : "memory");
        __syncthreads();
        if (lane == 0) {
            const unsigned epoch = (unsigned)(ticket / (unsigned long long)G);
            s_epoch = epoch;
            mbar_arrive(smem_u32(&s_epbar));
            int tail = 0;
            int nsent = 0;
            wait_counter(g_qready, (epoch + 1u) * (unsigned)G);
            while (nsent < 2) {
                int e;
                long long t0 = clock64();
                while ((e = ld_acquire_cta_s(smem_u32(&s_fifo[tail % FIFO_N]))) == EMPTY) {
                    __nanosleep(64);
                    if (clock64() - t0 > SPIN_LIMIT) __trap();
                }
                int ent[4];
                int cnt = 0;
                ent[0] = e; ent[1] = EMPTY; ent[2] = EMPTY; ent[3] = EMPTY;
                cnt = 1;
#pragma unroll
                for (int k = 1; k < 4; k++) {
                    if (cnt == k) {
                        int e2 = ld_acquire_cta_s(smem_u32(&s_fifo[(tail + k) % FIFO_N]));
                        if (e2 != EMPTY) { ent[k] = e2; cnt = k + 1; }
                    }
                }
                if (e != SENTINEL || cnt > 1) __threadfence();
#pragma unroll
                for (int k = 0; k < 4; k++) {
                    if (k < cnt) {
                        if (ent[k] == SENTINEL) nsent++;
                        else if (ent[k] < NHALF) red_add_gpu(cntK(ent[k] / UPP), 1u);
                        else { red_add_gpu(flagP(ent[k] - SIG_P), 1u); red_add_gpu(cntL(), 1u); }
                        st_release_cta_s(smem_u32(&s_fifo[(tail + k) % FIFO_N]), EMPTY);
                    }
                }
                tail += cnt;
            }
        }
    } else if (warp >= 8) {
        __syncthreads();
        if (cta < 112) {
            const int pt = tid - 256;
            const int kvh = cta / 14, cg = cta % 14;
            bar_sync(5, 384);
            {
                long long t0 = clock64();
                while (!*(volatile int*)&s_qok) {
                    __nanosleep(200);
                    if (clock64() - t0 > SPIN_LIMIT) __trap();
                }
            }
            {
                const char* src = (const char*)prm.wo + (size_t)kvh * 512 * (DM * 2) + cg * 64;
                uint64_t pol_ef;
                asm volatile("createpolicy.fractional.L2::evict_first.b64 %0, 1.0;" : "=l"(pol_ef));
#pragma unroll 4
                for (int i = 0; i < 16; i++) {
                    const int e = pt + 128 * i;
                    asm volatile("cp.async.cg.shared.global.L2::cache_hint [%0], [%1], 16, %2;" ::"r"(smem_u32(wo_s) + e * 16),
                                 "l"(src + (size_t)(e >> 2) * (DM * 2) + (e & 3) * 16), "l"(pol_ef)
                                 : "memory");
                }
                asm volatile("cp.async.wait_all;" ::: "memory");
            }
            if (pt == 0) {
                mbar_wait(smem_u32(&s_epbar), 0);
                wait_counter(g_qready, (s_epoch + 1u) * (unsigned)G);
                long long t0 = clock64();
                while (!*(volatile int*)&s_phase2) {
                    __nanosleep(500);
                    if (clock64() - t0 > SPIN_LIMIT) __trap();
                }
            }
            __syncwarp();
            const int cp = pt & 15, rg = pt >> 4;
            for (int b = 0; b < NB; b++) {
                const float4* src = g_O + (size_t)(b * 8 + kvh) * OVEC;
                long long t0 = clock64();
                if (warp == 8) {
                    while (!*(volatile int*)&s_sdone) {
                        float c = 0.f;
                        if (lane < NREP) c = ld_relaxed_v4(src + cg * 12 + (size_t)lane * NPAIR * OVEC).w;
#pragma unroll
                        for (int o = 1; o < NREP; o <<= 1) c += __shfl_xor_sync(0xffffffffu, c, o);
                        if (__shfl_sync(0xffffffffu, c, 0) == 128.0f) break;
                        __nanosleep(P_SLEEP);
                        if (clock64() - t0 > SPIN_LIMIT) __trap();
                    }
                }
                bar_sync(3, 128);
                float4 o[2];
                while (true) {
                    o[0] = o[1] = make_float4(0.f, 0.f, 0.f, 128.f);
                    if (pt < 96) {
                        float4 v[2][NREP];
#pragma unroll
                        for (int k = 0; k < 2; k++)
#pragma unroll
                            for (int rp = 0; rp < NREP; rp++) v[k][rp] = ld_relaxed_v4(src + pt + 96 * k + (size_t)rp * NPAIR * OVEC);
#pragma unroll
                        for (int k = 0; k < 2; k++) {
                            o[k] = v[k][0];
#pragma unroll
                            for (int rp = 1; rp < NREP; rp++) {
                                o[k].x += v[k][rp].x; o[k].y += v[k][rp].y; o[k].z += v[k][rp].z; o[k].w += v[k][rp].w;
                            }
                        }
                    }
                    if (bar_red_and(3, 128, o[0].w == 128.0f && o[1].w == 128.0f)) break;
                    if (clock64() - t0 > SPIN_LIMIT) __trap();
                }
                if (pt < 96) {
#pragma unroll
                    for (int k = 0; k < 2; k++) {
                        const int vi = pt + 96 * k, rr = vi % 48;
                        const int gg = rr < 32 ? (rr >> 2) : ((rr - 32) >> 1), sl = rr < 32 ? (rr & 3) : 4 + (rr & 1);
                        float* d = s_o + (vi / 48) * 64 + gg * 8;
                        if (sl < 4) { d[2 * sl] = bf16r(o[k].x); d[2 * sl + 1] = bf16r(o[k].y); d[256 + 2 * sl] = bf16r(o[k].z); }
                        else if (sl == 4) { d[257] = bf16r(o[k].x); d[259] = bf16r(o[k].y); d[261] = bf16r(o[k].z); }
                        else d[263] = bf16r(o[k].x);
                    }
                }
                bar_sync(3, 128);
                {
                    float a0 = 0.f, a1 = 0.f, a2 = 0.f, a3 = 0.f;
#pragma unroll 8
                    for (int i = 0; i < 64; i += 2) {
                        const uint32_t w0 = *(const uint32_t*)(wo_s + (i * 8 + rg) * 64 + cp * 4);
                        const uint32_t w1 = *(const uint32_t*)(wo_s + (i * 8 + 8 + rg) * 64 + cp * 4);
                        const float o0 = s_o[i * 8 + rg], o1 = s_o[i * 8 + 8 + rg];
                        a0 = fmaf(o0, bf_lo(w0), a0);
                        a1 = fmaf(o0, bf_hi(w0), a1);
                        a2 = fmaf(o1, bf_lo(w1), a2);
                        a3 = fmaf(o1, bf_hi(w1), a3);
                    }
                    a0 += a2;
                    a1 += a3;
                    a0 += __shfl_xor_sync(0xffffffffu, a0, 16);
                    a1 += __shfl_xor_sync(0xffffffffu, a1, 16);
                    if (lane < 16) *(float2*)(s_pr + (warp - 8) * 32 + cp * 2) = make_float2(a0, a1);
                }
                bar_sync(3, 128);
                if (pt < 16) {
                    float c0 = 0.f, c1 = 0.f;
#pragma unroll
                    for (int k = 0; k < 4; k++) {
                        const float2 p = *(const float2*)(s_pr + k * 32 + pt * 2);
                        c0 += p.x;
                        c1 += p.y;
                    }
                    red_add_v4((float*)(g_h + b * HVEC + cg * 16 + pt), c0, c1, 1.0f, 0.f);
                }
            }
        }
    } else {
        {
            float* s_xn = (float*)wo_s;
            float* s_red = (float*)(wo_s + 14336);
            const int c = tid & 3, r0 = tid >> 2;
            __syncthreads();
            if (cta < 128) {
                for (int k = tid; k < NREP * OVEC / 2; k += 256) g_O[cta * (NREP * OVEC / 2) + k] = make_float4(0.f, 0.f, 0.f, 0.f);
            } else if (cta == 128) {
                for (int k = tid; k < NB * HVEC; k += 256) g_h[k] = make_float4(0.f, 0.f, 0.f, 0.f);
            } else if (cta == 129) {
                if (tid < 129) g_cnt[tid * CPAD] = 0u;
            }
            if (cta < 128) {
                float v[14];
#pragma unroll
                for (int i = 0; i < 7; i++) {
                    v[2 * i] = bf_lo(xw[i]);
                    v[2 * i + 1] = bf_hi(xw[i]);
                }
                float shift = __shfl_sync(0xffffffffu, v[0], 0);
                float m, den;
                ln_stats(v, shift, m, den);
#pragma unroll
                for (int i = 0; i < 7; i++) {
                    float2 o = make_float2(ln_apply(v[2 * i], m, den), ln_apply(v[2 * i + 1], m, den));
                    *(float2*)(s_xn + warp * DM + 2 * (lane + 32 * i)) = o;
                }
                bar_sync(1, 256);
            }
            if (cta < 128) {
                float acc[8][8];
#pragma unroll
                for (int b = 0; b < 8; b++)
#pragma unroll
                    for (int e = 0; e < 8; e++) acc[b][e] = 0.f;
#pragma unroll
                for (int i = 0; i < 7; i++) {
                    float w[8];
                    w[0] = bf_lo(wv[i].x); w[1] = bf_hi(wv[i].x);
                    w[2] = bf_lo(wv[i].y); w[3] = bf_hi(wv[i].y);
                    w[4] = bf_lo(wv[i].z); w[5] = bf_hi(wv[i].z);
                    w[6] = bf_lo(wv[i].w); w[7] = bf_hi(wv[i].w);
#pragma unroll
                    for (int b = 0; b < 8; b++) {
                        float xv = s_xn[b * DM + r0 + 64 * i];
#pragma unroll
                        for (int e = 0; e < 8; e++) acc[b][e] = fmaf(xv, w[e], acc[b][e]);
                    }
                }
                const bool h4 = lane & 16, h3 = lane & 8, h2 = lane & 4;
                float a1[4][8], a2[2][8], a3[8];
#pragma unroll
                for (int b = 0; b < 4; b++)
#pragma unroll
                    for (int e = 0; e < 8; e++) {
                        float snd = h4 ? acc[b][e] : acc[b + 4][e];
                        float kp = h4 ? acc[b + 4][e] : acc[b][e];
                        a1[b][e] = kp + __shfl_xor_sync(0xffffffffu, snd, 16);
                    }
#pragma unroll
                for (int b = 0; b < 2; b++)
#pragma unroll
                    for (int e = 0; e < 8; e++) {
                        float snd = h3 ? a1[b][e] : a1[b + 2][e];
                        float kp = h3 ? a1[b + 2][e] : a1[b][e];
                        a2[b][e] = kp + __shfl_xor_sync(0xffffffffu, snd, 8);
                    }
#pragma unroll
                for (int e = 0; e < 8; e++) {
                    float snd = h2 ? a2[0][e] : a2[1][e];
                    float kp = h2 ? a2[1][e] : a2[0][e];
                    a3[e] = kp + __shfl_xor_sync(0xffffffffu, snd, 4);
                }
                const int bb = (h4 ? 4 : 0) + (h3 ? 2 : 0) + (h2 ? 1 : 0);
                float* dst = s_red + (warp * 8 + bb) * 32 + c * 8;
                *(float4*)dst = make_float4(a3[0], a3[1], a3[2], a3[3]);
                *(float4*)(dst + 4) = make_float4(a3[4], a3[5], a3[6], a3[7]);
                bar_sync(1, 256);
                if (tid < 128) {
                    mbar_wait(smem_u32(&s_epbar), 0);
                    const unsigned tag = s_epoch + 1u;
                    float s0 = 0.f, s1 = 0.f;
#pragma unroll
                    for (int w = 0; w < 8; w++) {
                        float2 p = *(const float2*)(s_red + w * 256 + tid * 2);
                        s0 += p.x;
                        s1 += p.y;
                    }
                    unsigned long long word = ((unsigned long long)tag << 32) | pack_bf16(s0, s1);
                    st_relaxed_64(g_q + (tid >> 4) * 2048 + cta * 16 + (tid & 15), word);
                    g_qp[(tid >> 4) * 2048 + cta * 16 + (tid & 15)] = (uint32_t)word;
                }
            }
            bar_sync(1, 256);
            if (cta < 112) asm volatile("bar.arrive 5, 384;" ::: "memory");
            if (tid == 128) {
                __threadfence();
                red_add_gpu(g_qready, 1u);
            }
        }

        if (warp < 4) {
            const int w = warp;
            const int r = lane & 7, mi = lane >> 3;
            const int g = lane >> 2, t = lane & 3;
            const bool diag = (t == (g >> 1));
            const uint32_t selLo = diag ? ((g & 1) ? 0x1044u : 0x4410u) : 0x4444u;
            const uint32_t selHi = diag ? ((g & 1) ? 0x3244u : 0x4432u) : 0x4444u;
            const uint32_t offA = (mi & 1) * 512 + (mi >> 1) * 128;
            const uint32_t offBK = (16 * w + r) * 512 + mi * 128;
            const uint32_t offBV = (8 * (mi & 1) + r) * 512 + w * 128;
            float4* Odst = g_O + (size_t)(cta % NREP) * NPAIR * OVEC + w * 48;
            int s = 0, ph = 0;
            while (true) {
                mbar_wait(smem_u32(&s_issued[s]), ph);
                const int u = s_unit[s];
                if (u >= 0) {
                    mbar_wait(smem_u32(&s_fullA[s]), ph);
                    const uint32_t tile = sm_tiles + s * TILE_BYTES;
                    const uint32_t aux = sm_aux + s * AUX_BYTES;
                    if (u < NHALF) {
                        mbar_wait(smem_u32(&s_fullT[s][(w * NSUB) / 4]), ph);
                        float acc[2][2][4];
#pragma unroll
                        for (int a = 0; a < 2; a++)
#pragma unroll
                            for (int b = 0; b < 2; b++)
#pragma unroll
                                for (int e = 0; e < 4; e++) acc[a][b][e] = 0.f;
#pragma unroll
                        for (int a = 0; a < 8; a++) {
                            const uint32_t rot = ((a + r) & 7) << 4;
                            uint32_t qa0[4], qa1[4], kb0[4], kb1[4];
                            ldsm4(qa0, aux + offA + rot);
                            ldsm4(qa1, aux + offA + 256 + rot);
                            ldsm4(kb0, tile + offBK + rot);
                            ldsm4(kb1, tile + offBK + 8 * 512 + rot);
                            mma16816(acc[0][0], qa0, kb0[0], kb0[1]);
                            mma16816(acc[0][1], qa1, kb0[2], kb0[3]);
                            mma16816(acc[1][0], qa0, kb1[0], kb1[1]);
                            mma16816(acc[1][1], qa1, kb1[2], kb1[3]);
                        }
                        if (diag) {
                            float v[4];
#pragma unroll
                            for (int nt = 0; nt < 2; nt++) {
                                float c0 = acc[nt][0][0] + acc[nt][1][0], c1 = acc[nt][0][1] + acc[nt][1][1];
                                float c2 = acc[nt][0][2] + acc[nt][1][2], c3 = acc[nt][0][3] + acc[nt][1][3];
                                v[2 * nt] = bf16r((g & 1) ? c1 : c0) * 0.0625f;
                                v[2 * nt + 1] = bf16r((g & 1) ? c3 : c2) * 0.0625f;
                            }
                            uint2 o = make_uint2(pack_bf16(v[0], v[1]), pack_bf16(v[2], v[3]));
                            *(uint2*)((char*)g_S + (size_t)u * 256 + w * 64 + g * 8) = o;
                        }
                    } else {
                        uint32_t pk[8];
#pragma unroll
                        for (int k = 0; k < 4; k++)
                            asm volatile("ld.shared.v2.u32 {%0,%1}, [%2];" : "=r"(pk[2 * k]), "=r"(pk[2 * k + 1]) : "r"(aux + k * 64 + g * 8) : "memory");
                        float acc[8][4];
#pragma unroll
                        for (int a = 0; a < 8; a++)
#pragma unroll
                            for (int e = 0; e < 4; e++) acc[a][e] = 0.f;
#pragma unroll
                        for (int k = 0; k < 4; k++) {
                            if ((k * NSUB) % 4 == 0) mbar_wait(smem_u32(&s_fullT[s][(k * NSUB) / 4]), ph);
                            uint32_t pa[4];
                            pa[0] = __byte_perm(pk[2 * k], 0u, selLo);
                            pa[1] = __byte_perm(pk[2 * k], 0u, selHi);
                            pa[2] = __byte_perm(pk[2 * k + 1], 0u, selLo);
                            pa[3] = __byte_perm(pk[2 * k + 1], 0u, selHi);
#pragma unroll
                            for (int cp = 0; cp < 4; cp++) {
                                const uint32_t rot = ((2 * cp + (mi >> 1) + r) & 7) << 4;
                                uint32_t vb[4];
                                ldsm4t(vb, tile + offBV + k * 16 * 512 + rot);
                                mma16816(acc[2 * cp], pa, vb[0], vb[1]);
                                mma16816(acc[2 * cp + 1], pa, vb[2], vb[3]);
                            }
                        }
                        const int l4 = (((g - 4) & 7) << 2) | t, l2 = (((g - 2) & 7) << 2) | t, l1 = (((g - 1) & 7) << 2) | t;
#pragma unroll
                        for (int c = 0; c < 4; c++)
#pragma unroll
                            for (int e = 0; e < 4; e++) acc[c][e] += __shfl_sync(0xffffffffu, acc[c + 4][e], l4);
#pragma unroll
                        for (int c = 0; c < 2; c++)
#pragma unroll
                            for (int e = 0; e < 4; e++) acc[c][e] += __shfl_sync(0xffffffffu, acc[c + 2][e], l2);
#pragma unroll
                        for (int e = 0; e < 4; e++) acc[0][e] += __shfl_sync(0xffffffffu, acc[1][e], l1);
                        float e1 = __shfl_down_sync(0xffffffffu, acc[0][3], 1), e2 = __shfl_down_sync(0xffffffffu, acc[0][3], 2);
                        float4* dst = Odst + (size_t)((u - NHALF) / UPP) * OVEC;
                        red_add_v4((float*)(dst + lane), acc[0][0], acc[0][1], acc[0][2], 1.0f);
                        if (t == 3) { e1 = 0.f; e2 = 0.f; }
                        if (t == 0 || t == 3) red_add_v4((float*)(dst + 32 + g * 2 + (t & 1)), acc[0][3], e1, e2, 1.0f);
                    }
                }
                __syncwarp();
                if (lane == 0) {
                    if (u < NHALF) {
                        int old = atom_add_acqrel_cta_s(smem_u32(&s_cnt[s]), 1);
                        if (old == 3) {
                            s_cnt[s] = 0;
                            fifo_push(s_fifo, &s_fifo_head, u);
                            if (u < 0) *(volatile int*)&s_sdone = 1;
                        }
                    }
                    mbar_arrive(smem_u32(&s_empty[s]));
                }
                if (u < 0) break;
                if (++s == RING) { s = 0; ph ^= 1; }
            }
        } else {
            const int at = tid - 128, aw = warp - 4;
            const unsigned char* mlp_s = wo_s + WO_BYTES;
            if (at == 0 && cta < 112) {
                mbar_expect_tx(smem_u32(&s_wobar), 3 * MLPW_BYTES + X_BYTES);
                bulk_load_nohint(smem_u32(mlp_s + 3 * MLPW_BYTES), prm.x, X_BYTES, smem_u32(&s_wobar));
                bulk_load_nohint(smem_u32(mlp_s), prm.w1, MLPW_BYTES, smem_u32(&s_wobar));
                bulk_load_nohint(smem_u32(mlp_s + MLPW_BYTES), prm.b1, MLPW_BYTES, smem_u32(&s_wobar));
                bulk_load_nohint(smem_u32(mlp_s + 2 * MLPW_BYTES), prm.w2, MLPW_BYTES, smem_u32(&s_wobar));
            }
            const float b2v = __bfloat162float(prm.b2[0]);
            if (at == 0) {
                mbar_wait(smem_u32(&s_epbar), 0);
                wait_counter(g_qready, (s_epoch + 1u) * (unsigned)G);
            }
            if (cta < 128 && !(cta & 1)) {
                const int job = cta >> 1;
                if (at == 0) {
                    const unsigned* c = cntK(job);
                    long long t0 = clock64();
                    while (ld_acquire_gpu(c) < (unsigned)UPP) {
                        __nanosleep(500);
                        if (clock64() - t0 > SPIN_LIMIT) __trap();
                    }
                }
                bar_sync(2, 128);
                uint4* Sp = g_S + (size_t)job * 2048 + at;
                uint4 v[16];
#pragma unroll
                for (int n = 0; n < 16; n++) v[n] = __ldcg(Sp + 128 * n);
                uint32_t mx = v[0].x;
#pragma unroll
                for (int n = 0; n < 16; n++) {
                    mx = hmax2_bf16(mx, hmax2_bf16(hmax2_bf16(v[n].x, v[n].y), hmax2_bf16(v[n].z, v[n].w)));
                }
#pragma unroll
                for (int o = 16; o > 0; o >>= 1) mx = hmax2_bf16(mx, __shfl_xor_sync(0xffffffffu, mx, o));
                if (lane == 0) s_redu[aw] = mx;
                bar_sync(2, 128);
                mx = hmax2_bf16(hmax2_bf16(s_redu[0], s_redu[1]), hmax2_bf16(s_redu[2], s_redu[3]));
                const float L2E = 1.4426950408889634f;
                const float m0 = bf_lo(mx), m1 = bf_hi(mx);
                float s0 = 0.f, s1 = 0.f;
#pragma unroll
                for (int n = 0; n < 16; n++) {
                    uint32_t ww[4] = {v[n].x, v[n].y, v[n].z, v[n].w};
#pragma unroll
                    for (int k = 0; k < 4; k++) {
                        s0 += ex2f((bf_lo(ww[k]) - m0) * L2E);
                        s1 += ex2f((bf_hi(ww[k]) - m1) * L2E);
                    }
                }
                s0 = warp_sum(s0);
                s1 = warp_sum(s1);
                if (lane == 0) { s_redf[aw] = s0; s_redf[4 + aw] = s1; }
                bar_sync(2, 128);
#pragma unroll
                for (int n = 0; n < 16; n++) asm volatile("" : "+r"(v[n].x), "+r"(v[n].y), "+r"(v[n].z), "+r"(v[n].w));
                const float i0 = __fdiv_rn(1.0f, (s_redf[0] + s_redf[1]) + (s_redf[2] + s_redf[3]));
                const float i1 = __fdiv_rn(1.0f, (s_redf[4] + s_redf[5]) + (s_redf[6] + s_redf[7]));
#pragma unroll
                for (int n = 0; n < 16; n++) {
                    uint32_t ww[4] = {v[n].x, v[n].y, v[n].z, v[n].w};
#pragma unroll
                    for (int k = 0; k < 4; k++) {
                        float p0 = ex2f((bf_lo(ww[k]) - m0) * L2E) * i0;
                        float p1 = ex2f((bf_hi(ww[k]) - m1) * L2E) * i1;
                        ww[k] = pack_bf16(p0, p1);
                    }
                    __stcg(Sp + 128 * n, make_uint4(ww[0], ww[1], ww[2], ww[3]));
                }
                bar_sync(2, 128);
                if (at == 0) {
                    fifo_push(s_fifo, &s_fifo_head, SIG_P + job);
                }
            }
            if (at == 0) fifo_push(s_fifo, &s_fifo_head, SENTINEL);
            if (cta < 112) {
                const bool act = at < 112;
                const int col = cta * 4 + aw;
                if (at == 0) {
                    long long t0 = clock64();
                    while (!*(volatile int*)&s_phase2) {
                        __nanosleep(500);
                        if (clock64() - t0 > SPIN_LIMIT) __trap();
                    }
                }
                mbar_wait(smem_u32(&s_wobar), 0);
                uint4 w1v[7], b1v[7], w2v[7];
#pragma unroll
                for (int i = 0; i < 7; i++) {
                    w1v[i] = *(const uint4*)(mlp_s + (lane + 32 * i) * 16);
                    b1v[i] = *(const uint4*)(mlp_s + MLPW_BYTES + (lane + 32 * i) * 16);
                    w2v[i] = *(const uint4*)(mlp_s + 2 * MLPW_BYTES + (lane + 32 * i) * 16);
                }
                for (int b = 0; b < NB; b++) {
                    const float4* hp = g_h + b * HVEC;
                    if (at == 0) {
                        long long t0 = clock64();
                        while (ld_relaxed_v4(hp + cta * 2).z != 8.0f) {
                            if (!*(volatile int*)&s_sdone) __nanosleep(P_SLEEP);
                            if (clock64() - t0 > SPIN_LIMIT) __trap();
                        }
                    }
                    bar_sync(2, 128);
                    float4 ha = make_float4(0.f, 0.f, 8.f, 0.f), hb = ha;
                    {
                        long long t0 = 0;
                        while (true) {
                            if (act) { ha = ld_relaxed_v4(hp + at * 2); hb = ld_relaxed_v4(hp + at * 2 + 1); }
                            if (bar_red_and(2, 128, ha.z == 8.0f && hb.z == 8.0f)) break;
                            if (t0 == 0) t0 = clock64();
                            if (clock64() - t0 > SPIN_LIMIT) __trap();
                        }
                    }
                    const uint2 xw = *(const uint2*)(mlp_s + 3 * MLPW_BYTES + b * DM * 2 + (act ? at : 0) * 8);
                    float v[4];
                    v[0] = bf16r(bf_lo(xw.x) + bf16r(ha.x));
                    v[1] = bf16r(bf_hi(xw.x) + bf16r(ha.y));
                    v[2] = bf16r(bf_lo(xw.y) + bf16r(hb.x));
                    v[3] = bf16r(bf_hi(xw.y) + bf16r(hb.y));
                    if (at == cta) *(float4*)s_hc = make_float4(v[0], v[1], v[2], v[3]);
                    float m1, d1, m2, d2;
                    ln_stats_block(v, aw, lane, s_ln, m1, d1);
#pragma unroll
                    for (int i = 0; i < 4; i++) v[i] = ln_apply(v[i], m1, d1);
                    ln_stats_block(v, aw, lane, s_ln + 8, m2, d2);
                    const float hc = s_hc[aw];
                    const float yc = ln_apply(ln_apply(hc, m1, d1), m2, d2);
                    const uint32_t hh = pack_bf16(yc, yc);
                    const float K0 = 0.7978845608028654f, K01 = 0.7978845608028654f * 0.044715f;
                    float acc0 = 0.f, acc1 = 0.f;
#pragma unroll
                    for (int i = 0; i < 7; i++) {
                        const uint32_t w1p[4] = {w1v[i].x, w1v[i].y, w1v[i].z, w1v[i].w};
                        const uint32_t b1p[4] = {b1v[i].x, b1v[i].y, b1v[i].z, b1v[i].w};
                        const uint32_t w2p[4] = {w2v[i].x, w2v[i].y, w2v[i].z, w2v[i].w};
#pragma unroll
                        for (int k = 0; k < 4; k++) {
                            uint32_t u2 = hadd2_bf16(hmul2_bf16(hh, w1p[k]), b1p[k]);
                            float ua = bf_lo(u2), ub = bf_hi(u2);
                            float za = ua * fmaf(ua * ua, K01, K0), zb = ub * fmaf(ub * ub, K01, K0);
                            float ga = fmaf(ua, tanh_fast(za), ua), gb = fmaf(ub, tanh_fast(zb), ub);
                            uint32_t gp = pack_bf16(ga, gb);
                            acc0 = fmaf(bf_lo(gp), bf_lo(w2p[k]), acc0);
                            acc1 = fmaf(bf_hi(gp), bf_hi(w2p[k]), acc1);
                        }
                    }
                    float y = 0.5f * warp_sum(acc0 + acc1);
                    if (lane == 0) {
                        float y2 = bf16r(bf16r(y) + b2v);
                        prm.out[b * DM + col] = __float2bfloat16_rn(hc + y2);
                    }
                }
            }
        }
    }
}

}

extern "C" void kernel_launch(void* const* d_in, const int* in_sizes, int n_in, void* d_out, int out_size) {
    (void)in_sizes; (void)n_in; (void)out_size;
    static int grid = 0;
    if (grid == 0) {
        int dev = 0, sms = 0;
        cudaGetDevice(&dev);
        cudaDeviceGetAttribute(&sms, cudaDevAttrMultiProcessorCount, dev);
        cudaFuncSetAttribute(fused_decode_kernel, cudaFuncAttributeMaxDynamicSharedMemorySize, SMEM_BYTES);
        grid = sms < 132 ? sms : 132;
    }
    Params p;
    p.x = (const __nv_bfloat16*)d_in[0];
    p.K = (const char*)d_in[1];
    p.V = (const char*)d_in[2];
    p.wq = (const __nv_bfloat16*)d_in[3];
    p.wo = (const __nv_bfloat16*)d_in[4];
    p.w1 = (const __nv_bfloat16*)d_in[6];
    p.b1 = (const __nv_bfloat16*)d_in[7];
    p.w2 = (const __nv_bfloat16*)d_in[8];
    p.b2 = (const __nv_bfloat16*)d_in[9];
    p.out = (__nv_bfloat16*)d_out;
    fused_decode_kernel<<<grid, NTHREADS, SMEM_BYTES>>>(p);
}
```
